```python
import torch

def _softmax(x, axis=-1):
    return torch.softmax(x, dim=axis)
def _gelu(x):
    return torch.nn.functional.gelu(x, approximate="tanh")
def _silu(x):
    return torch.nn.functional.silu(x)
def _sigmoid(x):
    return torch.sigmoid(x)
def _layernorm(x, axis=-1, eps=1e-5):
    m = x.mean(dim=axis, keepdim=True)
    v = x.var(dim=axis, keepdim=True, unbiased=False)
    return (x - m) / torch.sqrt(v + eps)
def _scatter_add(tgt, idx, src, axis=0):
    return tgt.clone().index_add_(axis, idx, src)
def _segment_sum(src, seg, n):
    out = torch.zeros((n,) + src.shape[1:], dtype=src.dtype)
    return out.index_add_(0, seg, src)
def _pad(x, pw):
    flat = tuple(v for pair in reversed(pw) for v in pair)
    return torch.nn.functional.pad(x, flat)

kernel_name = 'interleave_layers__linear_attn_block__dense_activation_relu__prompt'

def setup_inputs():

    _w = (lambda a: (lambda t: t.to(torch.bfloat16) if t.is_floating_point() else t)(torch.as_tensor(a)))
    def _A_setup():
        B, S, D = 1, 2048, 512
        return {
            "x": _w((lambda *s: torch.randn(*s, dtype=torch.bfloat16) * 0.05)(B, S, D)),
            "wqkv": _w((lambda *s: torch.randn(*s, dtype=torch.bfloat16) * 0.1)(D, 3 * D)),
            "wo": _w((lambda *s: torch.randn(*s, dtype=torch.bfloat16) * 0.05)(D, D)),
        }
    _A_in = _A_setup()

    def _B_setup():
        B, S, D, Dff = 1, 2048, 512, 1376
        return {
            "x": _w((lambda *s: torch.randn(*s, dtype=torch.bfloat16) * 0.05)(B, S, D)),
            "w1": _w((lambda *s: torch.randn(*s, dtype=torch.bfloat16) * 0.05)(D, Dff)),
            "w2": _w((lambda *s: torch.randn(*s, dtype=torch.bfloat16) * 0.05)(Dff, D)),
        }
    _B_in = _B_setup()

    return {
        "A_x": _A_in["x"],
        "A_wqkv": _A_in["wqkv"],
        "A_wo": _A_in["wo"],
        "B_x": _B_in["x"],
        "B_w1": _B_in["w1"],
        "B_w2": _B_in["w2"],
    }

def reference(A_x, A_wqkv, A_wo, B_x, B_w1, B_w2):
    def _A_ref(x, wqkv, wo):
        B, S, D = x.shape
        H = 32; Dh = D // H
        qkv = (lambda x, *d: x.permute(*d))((x @ wqkv).reshape(B, S, 3, H, Dh), 2, 0, 3, 1, 4)
        q, k, v = qkv[0], qkv[1], qkv[2]
        phi = lambda t: torch.where(t > 0, t + 1, torch.exp(t)) + 1e-6
        pq, pk = phi(q), phi(k)
        kv = torch.einsum("bhsd,bhse->bhde", pk, v)
        z = torch.einsum("bhsd->bhd", pk)
        num = torch.einsum("bhqd,bhde->bhqe", pq, kv)
        den = torch.einsum("bhqd,bhd->bhq", pq, z)[..., None] + 1e-6
        o = num / den
        return (lambda x, *d: x.permute(*d))(o, 0, 2, 1, 3).reshape(B, S, D) @ wo

    def _B_ref(x, w1, w2):
        h = torch.einsum("bsd,df->bsf", x, w1)
        zero = torch.zeros_like(h)
        h = torch.maximum(h, zero)
        return torch.einsum("bsf,fd->bsd", h, w2)

    x = A_x
    x = x + _A_ref(_layernorm(x, axis=-1), A_wqkv, A_wo)
    x = x + _B_ref(_layernorm(x, axis=-1), B_w1, B_w2)
    x = x + _A_ref(_layernorm(x, axis=-1), A_wqkv, A_wo)
    x = x + _B_ref(_layernorm(x, axis=-1), B_w1, B_w2)
    return x
```

```cpp
#include <cuda_runtime.h>
#include <cuda_bf16.h>
#include <cuda.h>
#include <stdint.h>

namespace {

constexpr int kS = 2048, kD = 512, kFF = 1376, kHS = 176;
constexpr uint32_t SM_RING = 131072, SLOT = 24576, SM_MISC = 229376;
constexpr uint32_t SM_STAT = SM_MISC;
constexpr uint32_t SM_CS = SM_MISC + 1024;
constexpr uint32_t SM_BAR = SM_CS + 1472;
constexpr uint32_t B_BFULL = SM_BAR, B_BEMPTY = SM_BAR + 32, B_AFULL = SM_BAR + 64  ,
                   B_AFREE = SM_BAR + 192  , B_OWN = SM_BAR + 240  , B_STAT = SM_BAR + 288  ,
                   B_CSDONE = SM_BAR + 304, B_CSRDY = SM_BAR + 312, B_KVDONE = SM_BAR + 320, B_KVRDY = SM_BAR + 328,
                   B_PRDY = SM_BAR + 336  , B_PFREE = SM_BAR + 352  ;
constexpr uint32_t SM_TOTAL = SM_BAR + 368;
static_assert(SM_TOTAL <= 232448, "smem");
constexpr uint32_t SPIN_LIMIT = 1u << 22;

__device__ uint32_t g_epoch[128 * 8];
__device__ uint32_t g_flags[32 * 32];
__device__ uint32_t g_cnt[3 * 8 * 32];
__device__ __align__(16) float g_cs[2 * 8 * 384];
__device__ __align__(16) float g_kv[2 * 2 * 8 * 1088];
__device__ __align__(128) float2 g_stats[4 * 32 * 64 * 8];
__device__ __align__(1024) uint4 g_act[3 * 32 * 8 * 512];
__device__ __align__(1024) uint4 g_h[32 * 8 * 3 * 512];
#define STAMP(role, i) do {} while (0)

__device__ __forceinline__ uint32_t smem_u32(const void* p) { return (uint32_t)__cvta_generic_to_shared(p); }
__device__ __forceinline__ void mbar_init(uint32_t bar, uint32_t cnt) { asm volatile("mbarrier.init.shared::cta.b64 [%0], %1;" :: "r"(bar), "r"(cnt)); }
__device__ __forceinline__ void mbar_expect_tx(uint32_t bar, uint32_t bytes) { asm volatile("mbarrier.arrive.expect_tx.shared::cta.b64 _, [%0], %1;" :: "r"(bar), "r"(bytes) : "memory"); }
__device__ __forceinline__ void mbar_arrive(uint32_t bar) { asm volatile("mbarrier.arrive.shared::cta.b64 _, [%0];" :: "r"(bar) : "memory"); }
__device__ __forceinline__ void mbar_arrive_remote(uint32_t bar) { asm volatile("mbarrier.arrive.shared::cluster.b64 _, [%0];" :: "r"(bar) : "memory"); }
__device__ __forceinline__ void mbar_wait(uint32_t bar, uint32_t parity) {
  asm volatile("{\n.reg .pred p;\n.reg .u32 c;\nmov.u32 c, 0;\nWAIT_LOOP:\n"
               "mbarrier.try_wait.parity.shared::cta.b64 p, [%0], %1;\n@p bra WAIT_DONE;\n"
               "add.u32 c, c, 1;\nsetp.lt.u32 p, c, %2;\n@p bra WAIT_LOOP;\ntrap;\nWAIT_DONE:\n}"
               :: "r"(bar), "r"(parity), "n"(SPIN_LIMIT) : "memory");
}
__device__ __forceinline__ uint32_t mapa(uint32_t addr, uint32_t rank) { uint32_t r; asm volatile("mapa.shared::cluster.u32 %0, %1, %2;" : "=r"(r) : "r"(addr), "r"(rank)); return r; }
__device__ __forceinline__ bool elect_one() { uint32_t p; asm volatile("{\n.reg .pred P;\nelect.sync _|P, 0xffffffff;\nselp.u32 %0, 1, 0, P;\n}" : "=r"(p)); return p; }
__device__ __forceinline__ void bulk_g2s(uint32_t dst, const void* src, uint32_t bytes, uint32_t bar) {
  asm volatile("cp.async.bulk.shared::cluster.global.mbarrier::complete_tx::bytes [%0], [%1], %2, [%3];" :: "r"(dst), "l"(src), "r"(bytes), "r"(bar) : "memory");
}
__device__ __forceinline__ void bulk_s2g(void* dst, uint32_t src, uint32_t bytes) { asm volatile("cp.async.bulk.global.shared::cta.bulk_group [%0], [%1], %2;" :: "l"(dst), "r"(src), "r"(bytes) : "memory"); }
__device__ __forceinline__ void bulk_commit() { asm volatile("cp.async.bulk.commit_group;" ::: "memory"); }
template <int N> __device__ __forceinline__ void bulk_wait() { asm volatile("cp.async.bulk.wait_group %0;" :: "n"(N) : "memory"); }
__device__ __forceinline__ void tma_load(uint32_t dst, const CUtensorMap* m, int c0, int c1, uint32_t bar) {
  asm volatile("cp.async.bulk.tensor.2d.shared::cluster.global.mbarrier::complete_tx::bytes [%0], [%1, {%3, %4}], [%2];" :: "r"(dst), "l"(m), "r"(bar), "r"(c0), "r"(c1) : "memory");
}
__device__ __forceinline__ void tma_store(const CUtensorMap* m, uint32_t src, int c0, int c1) {
  asm volatile("cp.async.bulk.tensor.2d.global.shared::cta.bulk_group [%0, {%2, %3}], [%1];" :: "l"(m), "r"(src), "r"(c0), "r"(c1) : "memory");
}
__device__ __forceinline__ void prefetch_l2(const void* p, uint32_t bytes) { asm volatile("cp.async.bulk.prefetch.L2.global [%0], %1;" :: "l"(p), "r"(bytes) : "memory"); }
__device__ __forceinline__ void prefetch_map(const CUtensorMap* m) { asm volatile("prefetch.tensormap [%0];" :: "l"(m) : "memory"); }
__device__ __forceinline__ void fence_async_smem() { asm volatile("fence.proxy.async.shared::cta;" ::: "memory"); }
__device__ __forceinline__ void fence_async_global() { asm volatile("fence.proxy.async.global;" ::: "memory"); }
__device__ __forceinline__ void fence_gpu() { asm volatile("fence.acq_rel.gpu;" ::: "memory"); }
__device__ __forceinline__ void st_release(uint32_t* p, uint32_t v) { asm volatile("st.release.gpu.global.u32 [%0], %1;" :: "l"(p), "r"(v) : "memory"); }
__device__ __forceinline__ uint32_t ld_acquire(const uint32_t* p) { uint32_t v; asm volatile("ld.acquire.gpu.global.u32 %0, [%1];" : "=r"(v) : "l"(p) : "memory"); return v; }
__device__ __forceinline__ uint32_t ld_relaxed(const uint32_t* p) { uint32_t v; asm volatile("ld.relaxed.gpu.global.u32 %0, [%1];" : "=r"(v) : "l"(p) : "memory"); return v; }
__device__ __forceinline__ float2 ld_relaxed_f2(const void* p) { float2 v; asm volatile("ld.relaxed.gpu.global.v2.f32 {%0,%1}, [%2];" : "=f"(v.x), "=f"(v.y) : "l"(p) : "memory"); return v; }
__device__ __forceinline__ float4 ld_relaxed_f4(const void* p) { float4 v; asm volatile("ld.relaxed.gpu.global.v4.f32 {%0,%1,%2,%3}, [%4];" : "=f"(v.x), "=f"(v.y), "=f"(v.z), "=f"(v.w) : "l"(p) : "memory"); return v; }
__device__ __forceinline__ void st_relaxed_b64(void* p, float a, uint32_t b) {
  asm volatile("{\n.reg .b64 v;\nmov.b64 v, {%1, %2};\nst.relaxed.gpu.global.b64 [%0], v;\n}" :: "l"(p), "r"(__float_as_uint(a)), "r"(b) : "memory");
}
__device__ __forceinline__ void red_add_u32(uint32_t* p, uint32_t v) { asm volatile("red.relaxed.gpu.global.add.u32 [%0], %1;" :: "l"(p), "r"(v) : "memory"); }
__device__ __forceinline__ void red_add_f2(float* p, float a, float b) { asm volatile("red.relaxed.gpu.global.add.v2.f32 [%0], {%1, %2};" :: "l"(p), "f"(a), "f"(b) : "memory"); }
__device__ __forceinline__ void red_add_f4(float* p, float a, float b, float c, float d) { asm volatile("red.relaxed.gpu.global.add.v4.f32 [%0], {%1, %2, %3, %4};" :: "l"(p), "f"(a), "f"(b), "f"(c), "f"(d) : "memory"); }
__device__ __forceinline__ void st_async_v4(uint32_t dst, uint32_t a, uint32_t b, uint32_t c, uint32_t d, uint32_t bar) {
  asm volatile("st.async.weak.shared::cluster.mbarrier::complete_tx::bytes.v4.b32 [%0], {%1,%2,%3,%4}, [%5];" :: "r"(dst), "r"(a), "r"(b), "r"(c), "r"(d), "r"(bar) : "memory");
}
__device__ __forceinline__ void stsm4(uint32_t addr, uint32_t a, uint32_t b, uint32_t c, uint32_t d) {
  asm volatile("stmatrix.sync.aligned.m8n8.x4.shared.b16 [%0], {%1,%2,%3,%4};" :: "r"(addr), "r"(a), "r"(b), "r"(c), "r"(d) : "memory");
}
__device__ __forceinline__ void ldsm4(uint32_t addr, uint32_t& a, uint32_t& b, uint32_t& c, uint32_t& d) {
  asm volatile("ldmatrix.sync.aligned.m8n8.x4.shared.b16 {%0,%1,%2,%3}, [%4];" : "=r"(a), "=r"(b), "=r"(c), "=r"(d) : "r"(addr) : "memory");
}
__device__ __forceinline__ void ldsm4t(uint32_t addr, uint32_t& a, uint32_t& b, uint32_t& c, uint32_t& d) {
  asm volatile("ldmatrix.sync.aligned.m8n8.x4.trans.shared.b16 {%0,%1,%2,%3}, [%4];" : "=r"(a), "=r"(b), "=r"(c), "=r"(d) : "r"(addr) : "memory");
}
__device__ __forceinline__ float2 lds_f2(uint32_t addr) { float2 v; asm volatile("ld.shared.v2.f32 {%0,%1}, [%2];" : "=f"(v.x), "=f"(v.y) : "r"(addr) : "memory"); return v; }
__device__ __forceinline__ uint2 lds_u2(uint32_t addr) { uint2 v; asm volatile("ld.shared.v2.u32 {%0,%1}, [%2];" : "=r"(v.x), "=r"(v.y) : "r"(addr) : "memory"); return v; }
__device__ __forceinline__ uint4 lds_u4(uint32_t addr) { uint4 v; asm volatile("ld.shared.v4.u32 {%0,%1,%2,%3}, [%4];" : "=r"(v.x), "=r"(v.y), "=r"(v.z), "=r"(v.w) : "r"(addr) : "memory"); return v; }
__device__ __forceinline__ void sts_f2(uint32_t addr, float a, float b) { asm volatile("st.shared.v2.f32 [%0], {%1,%2};" :: "r"(addr), "f"(a), "f"(b) : "memory"); }
__device__ __forceinline__ void sts_u2(uint32_t addr, uint32_t a, uint32_t b) { asm volatile("st.shared.v2.u32 [%0], {%1,%2};" :: "r"(addr), "r"(a), "r"(b) : "memory"); }
__device__ __forceinline__ void sts_f4(uint32_t addr, float4 v) { asm volatile("st.shared.v4.f32 [%0], {%1,%2,%3,%4};" :: "r"(addr), "f"(v.x), "f"(v.y), "f"(v.z), "f"(v.w) : "memory"); }
__device__ __forceinline__ void mma16816(float (&c)[4], uint32_t a0, uint32_t a1, uint32_t a2, uint32_t a3, uint32_t b0, uint32_t b1) {
  asm volatile("mma.sync.aligned.m16n8k16.row.col.f32.bf16.bf16.f32 {%0,%1,%2,%3}, {%4,%5,%6,%7}, {%8,%9}, {%0,%1,%2,%3};"
               : "+f"(c[0]), "+f"(c[1]), "+f"(c[2]), "+f"(c[3]) : "r"(a0), "r"(a1), "r"(a2), "r"(a3), "r"(b0), "r"(b1));
}
__device__ __forceinline__ uint32_t pack_bf16(float lo, float hi) { uint32_t r; asm("cvt.rn.bf16x2.f32 %0, %1, %2;" : "=r"(r) : "f"(hi), "f"(lo)); return r; }
__device__ __forceinline__ uint32_t pack_bf16_relu(float lo, float hi) { uint32_t r; asm("cvt.rn.relu.bf16x2.f32 %0, %1, %2;" : "=r"(r) : "f"(hi), "f"(lo)); return r; }
__device__ __forceinline__ float bf_lo(uint32_t v) { return __uint_as_float(v << 16); }
__device__ __forceinline__ float bf_hi(uint32_t v) { return __uint_as_float(v & 0xffff0000u); }
__device__ __forceinline__ float ex2(float x) { float y; asm("ex2.approx.ftz.f32 %0, %1;" : "=f"(y) : "f"(x)); return y; }
__device__ __forceinline__ float rcp(float x) { float y; asm("rcp.approx.ftz.f32 %0, %1;" : "=f"(y) : "f"(x)); return y; }
__device__ __forceinline__ float phi(float x) { float e = ex2(x * 1.4426950408889634f); return (x > 0.f ? x + 1.f : e) + 1e-6f; }
__device__ __forceinline__ void wg_fence() { asm volatile("wgmma.fence.sync.aligned;" ::: "memory"); }
__device__ __forceinline__ void wg_commit() { asm volatile("wgmma.commit_group.sync.aligned;" ::: "memory"); }
template <int N> __device__ __forceinline__ void wg_wait() { asm volatile("wgmma.wait_group.sync.aligned %0;" :: "n"(N) : "memory"); }
template <int N> __device__ __forceinline__ void fence_regs(float (&d)[N]) {
#pragma unroll
  for (int i = 0; i < N; i++) asm volatile("" : "+f"(d[i]) :: "memory");
}
template <int N> __device__ __forceinline__ void zero_regs(float (&d)[N]) {
#pragma unroll
  for (int i = 0; i < N; i++) d[i] = 0.f;
  fence_regs(d);
}
__device__ __forceinline__ void wg_bar(int wg) { if (wg == 0) asm volatile("bar.sync 1, 128;" ::: "memory"); else asm volatile("bar.sync 2, 128;" ::: "memory"); }
__device__ __forceinline__ uint64_t mk_desc(uint32_t addr, uint32_t lbo, uint32_t sbo, uint32_t swz) {
  return (uint64_t)((addr & 0x3FFFF) >> 4) | ((uint64_t)(lbo >> 4) << 16) | ((uint64_t)(sbo >> 4) << 32) | ((uint64_t)swz << 62);
}
__device__ __forceinline__ uint64_t descA(uint32_t addr) { return mk_desc(addr, 16, 1024, 1); }
__device__ __forceinline__ uint64_t descH(uint32_t addr) { return mk_desc(addr, 1024, 128, 0); }
__device__ __forceinline__ uint64_t descB(uint32_t addr, uint32_t lbo) { return mk_desc(addr, lbo, 1024, 1); }

__device__ __forceinline__ void wgmma_n64(float (&d)[32], uint64_t da, uint64_t db, int scale_d) {
  asm volatile("{\n.reg .pred p;\nsetp.ne.b32 p, %34, 0;\n"
    "wgmma.mma_async.sync.aligned.m64n64k16.f32.bf16.bf16 "
    "{%0, %1, %2, %3, %4, %5, %6, %7, %8, %9, %10, %11, %12, %13, %14, %15, "
    "%16, %17, %18, %19, %20, %21, %22, %23, %24, %25, %26, %27, %28, %29, %30, %31}, "
    "%32, %33, p, 1, 1, 0, 1;\n}"
    : "+f"(d[0]), "+f"(d[1]), "+f"(d[2]), "+f"(d[3]), "+f"(d[4]), "+f"(d[5]), "+f"(d[6]), "+f"(d[7]),
      "+f"(d[8]), "+f"(d[9]), "+f"(d[10]), "+f"(d[11]), "+f"(d[12]), "+f"(d[13]), "+f"(d[14]), "+f"(d[15]),
      "+f"(d[16]), "+f"(d[17]), "+f"(d[18]), "+f"(d[19]), "+f"(d[20]), "+f"(d[21]), "+f"(d[22]), "+f"(d[23]),
      "+f"(d[24]), "+f"(d[25]), "+f"(d[26]), "+f"(d[27]), "+f"(d[28]), "+f"(d[29]), "+f"(d[30]), "+f"(d[31])
    : "l"(da), "l"(db), "r"(scale_d));
}
__device__ __forceinline__ void wgmma_n128(float (&d)[32], float (&e)[32], uint64_t da, uint64_t db, int scale_d) {
  asm volatile("{\n.reg .pred p;\nsetp.ne.b32 p, %66, 0;\n"
    "wgmma.mma_async.sync.aligned.m64n128k16.f32.bf16.bf16 "
    "{%0, %1, %2, %3, %4, %5, %6, %7, %8, %9, %10, %11, %12, %13, %14, %15, "
    "%16, %17, %18, %19, %20, %21, %22, %23, %24, %25, %26, %27, %28, %29, %30, %31, "
    "%32, %33, %34, %35, %36, %37, %38, %39, %40, %41, %42, %43, %44, %45, %46, %47, "
    "%48, %49, %50, %51, %52, %53, %54, %55, %56, %57, %58, %59, %60, %61, %62, %63}, "
    "%64, %65, p, 1, 1, 0, 1;\n}"
    : "+f"(d[0]), "+f"(d[1]), "+f"(d[2]), "+f"(d[3]), "+f"(d[4]), "+f"(d[5]), "+f"(d[6]), "+f"(d[7]),
      "+f"(d[8]), "+f"(d[9]), "+f"(d[10]), "+f"(d[11]), "+f"(d[12]), "+f"(d[13]), "+f"(d[14]), "+f"(d[15]),
      "+f"(d[16]), "+f"(d[17]), "+f"(d[18]), "+f"(d[19]), "+f"(d[20]), "+f"(d[21]), "+f"(d[22]), "+f"(d[23]),
      "+f"(d[24]), "+f"(d[25]), "+f"(d[26]), "+f"(d[27]), "+f"(d[28]), "+f"(d[29]), "+f"(d[30]), "+f"(d[31]),
      "+f"(e[0]), "+f"(e[1]), "+f"(e[2]), "+f"(e[3]), "+f"(e[4]), "+f"(e[5]), "+f"(e[6]), "+f"(e[7]),
      "+f"(e[8]), "+f"(e[9]), "+f"(e[10]), "+f"(e[11]), "+f"(e[12]), "+f"(e[13]), "+f"(e[14]), "+f"(e[15]),
      "+f"(e[16]), "+f"(e[17]), "+f"(e[18]), "+f"(e[19]), "+f"(e[20]), "+f"(e[21]), "+f"(e[22]), "+f"(e[23]),
      "+f"(e[24]), "+f"(e[25]), "+f"(e[26]), "+f"(e[27]), "+f"(e[28]), "+f"(e[29]), "+f"(e[30]), "+f"(e[31])
    : "l"(da), "l"(db), "r"(scale_d));
}
__device__ __forceinline__ void wgmma_n176(float (&d)[88], uint64_t da, uint64_t db, int scale_d) {
  asm volatile("{\n.reg .pred p;\nsetp.ne.b32 p, %90, 0;\n"
    "wgmma.mma_async.sync.aligned.m64n176k16.f32.bf16.bf16 "
    "{%0, %1, %2, %3, %4, %5, %6, %7, %8, %9, %10, %11, %12, %13, %14, %15, "
    "%16, %17, %18, %19, %20, %21, %22, %23, %24, %25, %26, %27, %28, %29, %30, %31, "
    "%32, %33, %34, %35, %36, %37, %38, %39, %40, %41, %42, %43, %44, %45, %46, %47, "
    "%48, %49, %50, %51, %52, %53, %54, %55, %56, %57, %58, %59, %60, %61, %62, %63, "
    "%64, %65, %66, %67, %68, %69, %70, %71, %72, %73, %74, %75, %76, %77, %78, %79, "
    "%80, %81, %82, %83, %84, %85, %86, %87}, "
    "%88, %89, p, 1, 1, 0, 1;\n}"
    : "+f"(d[0]), "+f"(d[1]), "+f"(d[2]), "+f"(d[3]), "+f"(d[4]), "+f"(d[5]), "+f"(d[6]), "+f"(d[7]),
      "+f"(d[8]), "+f"(d[9]), "+f"(d[10]), "+f"(d[11]), "+f"(d[12]), "+f"(d[13]), "+f"(d[14]), "+f"(d[15]),
      "+f"(d[16]), "+f"(d[17]), "+f"(d[18]), "+f"(d[19]), "+f"(d[20]), "+f"(d[21]), "+f"(d[22]), "+f"(d[23]),
      "+f"(d[24]), "+f"(d[25]), "+f"(d[26]), "+f"(d[27]), "+f"(d[28]), "+f"(d[29]), "+f"(d[30]), "+f"(d[31]),
      "+f"(d[32]), "+f"(d[33]), "+f"(d[34]), "+f"(d[35]), "+f"(d[36]), "+f"(d[37]), "+f"(d[38]), "+f"(d[39]),
      "+f"(d[40]), "+f"(d[41]), "+f"(d[42]), "+f"(d[43]), "+f"(d[44]), "+f"(d[45]), "+f"(d[46]), "+f"(d[47]),
      "+f"(d[48]), "+f"(d[49]), "+f"(d[50]), "+f"(d[51]), "+f"(d[52]), "+f"(d[53]), "+f"(d[54]), "+f"(d[55]),
      "+f"(d[56]), "+f"(d[57]), "+f"(d[58]), "+f"(d[59]), "+f"(d[60]), "+f"(d[61]), "+f"(d[62]), "+f"(d[63]),
      "+f"(d[64]), "+f"(d[65]), "+f"(d[66]), "+f"(d[67]), "+f"(d[68]), "+f"(d[69]), "+f"(d[70]), "+f"(d[71]),
      "+f"(d[72]), "+f"(d[73]), "+f"(d[74]), "+f"(d[75]), "+f"(d[76]), "+f"(d[77]), "+f"(d[78]), "+f"(d[79]),
      "+f"(d[80]), "+f"(d[81]), "+f"(d[82]), "+f"(d[83]), "+f"(d[84]), "+f"(d[85]), "+f"(d[86]), "+f"(d[87])
    : "l"(da), "l"(db), "r"(scale_d));
}

__device__ __forceinline__ void publish_stats(const uint32_t (&xr)[16], float2* dst  , int t, uint32_t tag) {
  float s0 = 0.f, s1 = 0.f;
#pragma unroll
  for (int j = 0; j < 8; j++) { s0 += bf_lo(xr[2 * j]) + bf_hi(xr[2 * j]); s1 += bf_lo(xr[2 * j + 1]) + bf_hi(xr[2 * j + 1]); }
  s0 += __shfl_xor_sync(0xffffffff, s0, 1); s1 += __shfl_xor_sync(0xffffffff, s1, 1);
  s0 += __shfl_xor_sync(0xffffffff, s0, 2); s1 += __shfl_xor_sync(0xffffffff, s1, 2);
  const float m0 = s0 * (1.f / 64.f), m1 = s1 * (1.f / 64.f);
  float q0 = 0.f, q1 = 0.f;
#pragma unroll
  for (int j = 0; j < 8; j++) {
    float a = bf_lo(xr[2 * j]) - m0, b = bf_hi(xr[2 * j]) - m0, c = bf_lo(xr[2 * j + 1]) - m1, d = bf_hi(xr[2 * j + 1]) - m1;
    q0 = fmaf(a, a, q0); q0 = fmaf(b, b, q0); q1 = fmaf(c, c, q1); q1 = fmaf(d, d, q1);
  }
  q0 += __shfl_xor_sync(0xffffffff, q0, 1); q1 += __shfl_xor_sync(0xffffffff, q1, 1);
  q0 += __shfl_xor_sync(0xffffffff, q0, 2); q1 += __shfl_xor_sync(0xffffffff, q1, 2);
  if (t == 0) {
    st_relaxed_b64(dst, s0, (__float_as_uint(q0) & ~1u) | tag);
    st_relaxed_b64(dst + 64, s1, (__float_as_uint(q1) & ~1u) | tag);
  }
}

__device__ __forceinline__ void gather_stats(const float2* src  , uint32_t sm_dst, uint32_t bar, int lane, uint32_t tag) {
#pragma unroll 1
  for (int rr = 0; rr < 2; rr++) {
    const float2* p = src + (rr * 32 + lane) * 8;
    float4 v0, v1, v2, v3;
    uint32_t cnt = 0;
    while (true) {
      v0 = ld_relaxed_f4(p); v1 = ld_relaxed_f4(p + 2); v2 = ld_relaxed_f4(p + 4); v3 = ld_relaxed_f4(p + 6);
      uint32_t bad = ((__float_as_uint(v0.y) ^ tag) | (__float_as_uint(v0.w) ^ tag) | (__float_as_uint(v1.y) ^ tag) | (__float_as_uint(v1.w) ^ tag) |
                      (__float_as_uint(v2.y) ^ tag) | (__float_as_uint(v2.w) ^ tag) | (__float_as_uint(v3.y) ^ tag) | (__float_as_uint(v3.w) ^ tag)) & 1u;
      if (__all_sync(0xffffffff, bad == 0)) break;
      if (++cnt > SPIN_LIMIT) __trap();
    }
    const float mean = (v0.x + v0.z + v1.x + v1.z + v2.x + v2.z + v3.x + v3.z) * (1.f / 512.f);
    float m2 = v0.y + v0.w + v1.y + v1.w + v2.y + v2.w + v3.y + v3.w;
    float d, b = 0.f;
    d = v0.x * (1.f / 64.f) - mean; b = fmaf(d, d, b); d = v0.z * (1.f / 64.f) - mean; b = fmaf(d, d, b);
    d = v1.x * (1.f / 64.f) - mean; b = fmaf(d, d, b); d = v1.z * (1.f / 64.f) - mean; b = fmaf(d, d, b);
    d = v2.x * (1.f / 64.f) - mean; b = fmaf(d, d, b); d = v2.z * (1.f / 64.f) - mean; b = fmaf(d, d, b);
    d = v3.x * (1.f / 64.f) - mean; b = fmaf(d, d, b); d = v3.z * (1.f / 64.f) - mean; b = fmaf(d, d, b);
    m2 = fmaf(b, 64.f, m2);
    sts_f2(sm_dst + (rr * 32 + lane) * 8, rsqrtf(m2 * (1.f / 512.f) + 1e-5f), -mean);
  }
  __syncwarp();
  if (lane == 0) mbar_arrive(bar);
}

__device__ __forceinline__ void wait_flag(const uint32_t* f, uint32_t ev) {
  uint32_t cnt = 0;
  while ((int32_t)(ld_acquire(f) - ev) < 0) { if (++cnt > SPIN_LIMIT) __trap(); }
}

__device__ __forceinline__ void all_gather(uint4* gbuf  , uint32_t* flags, uint32_t abase, uint32_t afull, int r, uint32_t ev, int lane) {
  if (elect_one()) {
    bulk_s2g(gbuf + r * 512, abase, 8192); bulk_commit(); bulk_wait<0>();
    st_release(flags + r, ev);
  }
  __syncwarp();
  uint32_t todo = 0xfe, cnt = 0;
  while (todo) {
    const uint32_t f = ld_acquire(flags + ((r + lane) & 7));
    uint32_t rdy = __ballot_sync(0xffffffff, (int32_t)(f - ev) >= 0) & todo;
    if (rdy) {
      if (elect_one()) {
        fence_async_global();
        uint32_t m = rdy;
        while (m) {
          const int i = __ffs(m) - 1; m &= m - 1;
          mbar_expect_tx(afull + i * 8, 8192);
          bulk_g2s(abase + i * 8192, gbuf + ((r + i) & 7) * 512, 8192, afull + i * 8);
        }
      }
      __syncwarp();
      todo &= ~rdy;
    }
    if (++cnt > SPIN_LIMIT) __trap();
  }
}

__global__ void __cluster_dims__(2, 1, 1) __launch_bounds__(384, 1)
fused_kernel(const __grid_constant__ CUtensorMap tm_x, const __grid_constant__ CUtensorMap tm_out,
             const __grid_constant__ CUtensorMap tm_wqkv, const __grid_constant__ CUtensorMap tm_wo,
             const __grid_constant__ CUtensorMap tm_w1, const __grid_constant__ CUtensorMap tm_w2,
             const __nv_bfloat16* __restrict__ wqkv, const __nv_bfloat16* __restrict__ wo,
             const __nv_bfloat16* __restrict__ w1, const __nv_bfloat16* __restrict__ w2) {
  extern __shared__ __align__(1024) uint8_t smem_raw[];
  const uint32_t sb = smem_u32(smem_raw);
  const int tid = threadIdx.x, lane = tid & 31;
  const int warp = __shfl_sync(0xffffffff, tid >> 5, 0);
  const int bid = blockIdx.x, cb = bid >> 3, r = bid & 7;

  if (tid == 0) {
    if (sb & 1023) __trap();
    for (int i = 0; i < 4; i++) { mbar_init(sb + B_BFULL + i * 8, 1); mbar_init(sb + B_BEMPTY + i * 8, 8); }
    for (int i = 0; i < 16; i++) mbar_init(sb + B_AFULL + i * 8, 1);
    for (int i = 0; i < 6; i++) { mbar_init(sb + B_AFREE + i * 8, 4); mbar_init(sb + B_OWN + i * 8, 4); }
    for (int i = 0; i < 2; i++) { mbar_init(sb + B_STAT + i * 8, 1); mbar_init(sb + B_PRDY + i * 8, 1); mbar_init(sb + B_PFREE + i * 8, 4); }
    mbar_init(sb + B_CSDONE, 6); mbar_init(sb + B_CSRDY, 1); mbar_init(sb + B_KVDONE, 8); mbar_init(sb + B_KVRDY, 1);
    asm volatile("fence.mbarrier_init.release.cluster;" ::: "memory");
  }
  const uint32_t epoch = ld_relaxed(g_epoch + bid * 8);
  __syncthreads();
  asm volatile("barrier.cluster.arrive.relaxed.aligned;" ::: "memory");

  if (warp >= 8) {
  asm volatile("setmaxnreg.dec.sync.aligned.u32 72;");
  if (warp == 8) {
    uint32_t st = 0;
    auto acquire = [&](uint32_t bytes) -> uint32_t {
      const uint32_t s = st & 3;
      mbar_wait(sb + B_BEMPTY + s * 8, ((st >> 2) & 1) ^ 1);
      st++;
      return s;
    };
    if (lane == 0) { prefetch_map(&tm_wqkv); prefetch_map(&tm_wo); prefetch_map(&tm_w1); prefetch_map(&tm_w2); }
#pragma unroll 1
    for (int l = 0; l < 2; l++) {
#pragma unroll 1
      for (int i = 0; i < 8; i++) {
        const uint32_t s = acquire(0), dst = sb + SM_RING + s * SLOT, fb = sb + B_BFULL + s * 8;
        const int kc = (r + i) & 7;
        if (elect_one()) { mbar_expect_tx(fb, 16384); tma_load(dst, &tm_wqkv, 512 + 64 * r, 64 * kc, fb); tma_load(dst + 8192, &tm_wqkv, 1024 + 64 * r, 64 * kc, fb); }
      }
#pragma unroll 1
      for (int i = 0; i < 4; i++) {
        const uint32_t s = acquire(0), dst = sb + SM_RING + s * SLOT, fb = sb + B_BFULL + s * 8;
        if (elect_one()) { mbar_expect_tx(fb, 16384); tma_load(dst, &tm_wqkv, 64 * r, 64 * ((r + 2 * i) & 7), fb); tma_load(dst + 8192, &tm_wqkv, 64 * r, 64 * ((r + 2 * i + 1) & 7), fb); }
      }
#pragma unroll 1
      for (int i = 0; i < 4; i++) {
        const uint32_t s = acquire(0), dst = sb + SM_RING + s * SLOT, fb = sb + B_BFULL + s * 8;
        if (elect_one()) { mbar_expect_tx(fb, 16384); tma_load(dst, &tm_wo, 64 * r, 64 * ((r + 2 * i) & 7), fb); tma_load(dst + 8192, &tm_wo, 64 * r, 64 * ((r + 2 * i + 1) & 7), fb); }
      }
#pragma unroll 1
      for (int i = 0; i < 8; i++) {
        const uint32_t s = acquire(0), dst = sb + SM_RING + s * SLOT, fb = sb + B_BFULL + s * 8;
        const int kc = (r + i) & 7;
        if (elect_one()) { mbar_expect_tx(fb, 24576); tma_load(dst, &tm_w1, kHS * r, 64 * kc, fb); tma_load(dst + 8192, &tm_w1, kHS * r + 64, 64 * kc, fb); tma_load(dst + 16384, &tm_w1, kHS * r + 128, 64 * kc, fb); }
      }
#pragma unroll 1
      for (int i = 0; i < 8; i++) {
        const uint32_t s = acquire(0), dst = sb + SM_RING + s * SLOT, fb = sb + B_BFULL + s * 8;
        const int j = (r + (i & ~1)) & 7;
        if (elect_one()) { mbar_expect_tx(fb, kHS * 128); tma_load(dst, &tm_w2, 64 * ((i & 1) ? r : (r ^ 1)), kHS * j, fb); }
      }
    }
    asm volatile("barrier.cluster.wait.aligned;" ::: "memory");
  } else if (warp == 9 || warp == 10) {
    const int h = warp - 9, half = cb * 2 + h;
    const uint32_t abase = sb + h * 65536, afull = sb + B_AFULL + h * 64, afree = sb + B_AFREE + h * 24, own = sb + B_OWN + h * 24;
    uint32_t* flags = g_flags + half * 32;
    if (elect_one()) {
      prefetch_map(&tm_x);
      for (int i = 0; i < 8; i++) { mbar_expect_tx(afull + i * 8, 8192); tma_load(abase + i * 8192, &tm_x, 64 * ((r + i) & 7), 128 * cb + 64 * h, afull + i * 8); }
    }
    __syncwarp();
    const uint32_t ev0 = epoch * 16, tag = (epoch + 1) & 1;
    gather_stats(g_stats + (0 * 32 + half) * 512, sb + SM_STAT + h * 512, sb + B_STAT + h * 8, lane, tag);
    asm volatile("barrier.cluster.wait.aligned;" ::: "memory");
    uint32_t p0 = 0;
    uint32_t po = 0;
#pragma unroll 1
    for (int l = 0; l < 2; l++) {
      const uint32_t ev = ev0 + l * 6;
      mbar_wait(afree, p0); p0 ^= 1; mbar_wait(own, po); po ^= 1;
      STAMP(2 + h, l * 16 + 0);
      all_gather(g_act + (0 * 32 + half) * 4096, flags, abase, afull, r, ev + 1, lane);
      STAMP(2 + h, l * 16 + 1);
      mbar_wait(afree, p0); p0 ^= 1; mbar_wait(own, po); po ^= 1;
      STAMP(2 + h, l * 16 + 2);
      all_gather(g_act + (1 * 32 + half) * 4096, flags, abase, afull, r, ev + 2, lane);
      STAMP(2 + h, l * 16 + 3);
      gather_stats(g_stats + ((2 * l + 1) * 32 + half) * 512, sb + SM_STAT + h * 512, sb + B_STAT + h * 8, lane, tag);
      STAMP(2 + h, l * 16 + 4);
      mbar_wait(afree, p0); p0 ^= 1;
      uint4* hb = g_h + half * 8 * 1536;
      mbar_wait(own, po); po ^= 1;
      STAMP(2 + h, l * 16 + 5);
      if (lane == 0) { bulk_s2g(hb + r * 1536, abase, 8192); bulk_commit(); }
      mbar_wait(own + 8, l);
      if (lane == 0) { bulk_s2g(hb + r * 1536 + 512, abase + 8192, 8192); bulk_commit(); }
      mbar_wait(own + 16, l);
      if (lane == 0) {
        bulk_s2g(hb + r * 1536 + 1024, abase + 16384, 6144); bulk_commit();
        bulk_wait<2>(); st_release(flags + r, ev + 3);
        bulk_wait<0>(); st_release(flags + r, ev + 5);
      }
      __syncwarp();
      STAMP(2 + h, l * 16 + 6);
#pragma unroll 1
      for (int b = 3; b < 12; b++) {
        const int t = b / 3, bb = b - 3 * t, j = (r + 2 * t) & 7, slot = b & 7;
        if (b == 8) mbar_wait(afree + 8, l);
        if (b == 11) mbar_wait(afree + 16, l);
        if (bb < 2) wait_flag(flags + j, ev + (bb == 0 ? 3 : 5));
        if (elect_one()) {
          const uint32_t bytes = bb == 2 ? 6144 : 8192;
          fence_async_global();
          mbar_expect_tx(afull + slot * 8, bytes);
          bulk_g2s(abase + slot * 8192, hb + j * 1536 + bb * 512, bytes, afull + slot * 8);
        }
        __syncwarp();
      }
      STAMP(2 + h, l * 16 + 7);
      mbar_wait(afree, p0); p0 ^= 1; mbar_wait(own, po); po ^= 1;
      STAMP(2 + h, l * 16 + 8);
      if (l == 0) {
        all_gather(g_act + (2 * 32 + half) * 4096, flags, abase, afull, r, ev + 6, lane);
        STAMP(2 + h, l * 16 + 9);
        gather_stats(g_stats + (2 * 32 + half) * 512, sb + SM_STAT + h * 512, sb + B_STAT + h * 8, lane, tag);
      } else if (lane == 0) {
        tma_store(&tm_out, abase, 64 * r, 128 * cb + 64 * h); bulk_commit(); bulk_wait<0>();
      }
      STAMP(2 + h, l * 16 + 10);
    }
  } else {
    if (lane == 0) prefetch_l2((const char*)wqkv + bid * 12288, 12288);
    if (lane == 1) prefetch_l2((const char*)wo + bid * 4096, 4096);
    if (lane == 2) prefetch_l2((const char*)w2 + bid * 11008, 11008);
    const uint32_t par = epoch & 1;
    if (lane < 24) g_cs[((par ^ 1) * 8 + r) * 384 + cb * 24 + lane] = 0.f;
    for (int i = lane; i < 136; i += 32) g_kv[(((par ^ 1) * 2 + (i >= 68)) * 8 + r) * 1088 + cb * 68 + (i >= 68 ? i - 68 : i)] = 0.f;
    asm volatile("barrier.cluster.wait.aligned;" ::: "memory");
    const uint32_t target = (epoch + 1) * 16;
    mbar_wait(sb + B_CSDONE, 0);
    if (lane == 0) { fence_gpu(); red_add_u32(g_cnt + (0 * 8 + r) * 32, 1); }
    wait_flag(g_cnt + (0 * 8 + r) * 32, target);
    for (int i = lane; i < 92; i += 32) sts_f4(sb + SM_CS + i * 16, ld_relaxed_f4(g_cs + (par * 8 + r) * 384 + i * 4));
    __syncwarp();
    if (lane == 0) mbar_arrive(sb + B_CSRDY);
    const int g = lane >> 2, t = lane & 3;
#pragma unroll 1
    for (int l = 0; l < 2; l++) {
      mbar_wait(sb + B_KVDONE, l);
      if (lane == 0) { fence_gpu(); red_add_u32(g_cnt + ((1 + l) * 8 + r) * 32, 1); }
      wait_flag(g_cnt + ((1 + l) * 8 + r) * 32, target);
      const float* kv = g_kv + ((par * 2 + l) * 8 + r) * 1088;
      float2 v[24];
#pragma unroll
      for (int hh = 0; hh < 4; hh++) {
        v[hh * 6 + 0] = ld_relaxed_f2(kv + hh * 272 + g * 16 + 2 * t);        v[hh * 6 + 1] = ld_relaxed_f2(kv + hh * 272 + g * 16 + 8 + 2 * t);
        v[hh * 6 + 2] = ld_relaxed_f2(kv + hh * 272 + (8 + g) * 16 + 2 * t);  v[hh * 6 + 3] = ld_relaxed_f2(kv + hh * 272 + (8 + g) * 16 + 8 + 2 * t);
        v[hh * 6 + 4] = ld_relaxed_f2(kv + hh * 272 + 256 + 2 * t);           v[hh * 6 + 5] = ld_relaxed_f2(kv + hh * 272 + 256 + 8 + 2 * t);
      }
#pragma unroll
      for (int i = 0; i < 12; i++) sts_u2(sb + SM_RING + 16384 + i * 256 + lane * 8, pack_bf16(v[2 * i].x, v[2 * i].y), pack_bf16(v[2 * i + 1].x, v[2 * i + 1].y));
      __syncwarp();
      if (lane == 0) mbar_arrive(sb + B_KVRDY);
    }
    if (lane == 0) g_epoch[bid * 8] = epoch + 1;
  }
  } else {
    asm volatile("setmaxnreg.inc.sync.aligned.u32 216;");
    const int wg = warp >> 2, wq = warp & 3, g = lane >> 2, t = lane & 3, half = cb * 2 + wg;
    const uint32_t abase = sb + wg * 65536, afull = sb + B_AFULL + wg * 64, afree = sb + B_AFREE + wg * 24, own = sb + B_OWN + wg * 24;
    const uint32_t ring = sb + SM_RING;
    const int mrow = 16 * wq + 8 * ((lane >> 3) & 1) + (lane & 7);
    const uint32_t sw_row = mrow * 128, sw_x = lane & 7, sw_hi = lane >> 4;
    auto sw_addr = [&](uint32_t base, int s) -> uint32_t { return base + sw_row + (((2 * s + sw_hi) ^ sw_x) << 4); };
    STAMP(wg, 62);
    if (warp < 6) {
      const int cg = lane & 7, rg = lane >> 3;
      const __nv_bfloat16* p; int pitch; bool ok = true;
      if (warp < 3) { p = wqkv + warp * 512 + 64 * r + 8 * cg; pitch = 1536; }
      else { const int col = 64 * (warp - 3) + 8 * cg; ok = col < kHS && kHS * r + col < kFF; p = w1 + kHS * r + col; pitch = kFF; }
      float a[8];
#pragma unroll
      for (int i = 0; i < 8; i++) a[i] = 0.f;
      if (ok) {
        uint4 v[8];
#pragma unroll
        for (int i = 0; i < 8; i++) v[i] = __ldg((const uint4*)(p + (size_t)(32 * cb + 4 * i + rg) * pitch));
#pragma unroll
        for (int i = 0; i < 8; i++) {
          a[0] += bf_lo(v[i].x); a[1] += bf_hi(v[i].x); a[2] += bf_lo(v[i].y); a[3] += bf_hi(v[i].y);
          a[4] += bf_lo(v[i].z); a[5] += bf_hi(v[i].z); a[6] += bf_lo(v[i].w); a[7] += bf_hi(v[i].w);
        }
      }
#pragma unroll
      for (int i = 0; i < 8; i++) { a[i] += __shfl_xor_sync(0xffffffff, a[i], 8); a[i] += __shfl_xor_sync(0xffffffff, a[i], 16); }
      if (rg == 0 && ok) {
        float* d = g_cs + ((epoch & 1) * 8 + r) * 384 + warp * 64 + 8 * cg;
        red_add_f4(d, a[0], a[1], a[2], a[3]); red_add_f4(d + 4, a[4], a[5], a[6], a[7]);
      }
      __syncwarp();
      if (lane == 0) mbar_arrive(sb + B_CSDONE);
    }
    asm volatile("barrier.cluster.wait.aligned;" ::: "memory");
    const uint32_t tag = (epoch + 1) & 1;
    uint32_t xr[16];
    uint32_t aph = 0;
    uint32_t st = 0;
    uint32_t sph = 0;
    auto wait_a = [&](int i) { mbar_wait(afull + i * 8, (aph >> i) & 1); aph ^= 1u << i; };
    auto wait_b = [&]() -> uint32_t { const uint32_t s = st & 3; mbar_wait(sb + B_BFULL + s * 8, (st >> 2) & 1); st++; return ring + s * SLOT; };
    auto release_b = [&](uint32_t idx) { if (lane == 0) mbar_arrive(sb + B_BEMPTY + (idx & 3) * 8); };
    auto signal = [&](uint32_t bar) { __syncwarp(); if (lane == 0) mbar_arrive(bar); };
    float2* stat_dst = g_stats + half * 512 + (16 * wq + g) * 8 + r;
    const uint32_t stat_sm = sb + SM_STAT + (wg * 64 + 16 * wq + g) * 8;

    wait_a(0);
#pragma unroll
    for (int s = 0; s < 4; s++) ldsm4(sw_addr(abase, s), xr[4 * s], xr[4 * s + 1], xr[4 * s + 2], xr[4 * s + 3]);
    publish_stats(xr, stat_dst, t, tag);
    STAMP(wg, 63);

#pragma unroll 1
    for (int l = 0; l < 2; l++) {
      float rs0, rs1;
      {
        float ak[32], av[32], aq[32];
        zero_regs(ak); zero_regs(av); zero_regs(aq);
        STAMP(wg, l * 24 + 0);
#pragma unroll 1
        for (int i = 0; i < 8; i++) {
          if (i > 0) wait_a(i);
          const uint32_t bs = wait_b();
          const uint64_t da = descA(abase + i * 8192), db = descB(bs, 8192);
          wg_fence();
#pragma unroll
          for (int k = 0; k < 4; k++) wgmma_n128(ak, av, da + 2 * k, db + 128 * k, (i | k) != 0);
          wg_commit();
          if (i == 0 && l == 1) publish_stats(xr, stat_dst + 2 * 32 * 512, t, tag);
          if (i > 0) { wg_wait<1>(); release_b(st - 2); }
        }
        STAMP(wg, l * 24 + 1);
#pragma unroll
        for (int i = 0; i < 3; i++) {
          const uint32_t bs = wait_b();
          const uint64_t da = descA(abase + i * 16384), db = descB(bs, 8192);
          wg_fence();
#pragma unroll
          for (int k = 0; k < 8; k++) wgmma_n64(aq, da + (k >> 2) * 512 + 2 * (k & 3), db + 128 * k, (i | k) != 0);
          wg_commit();
          if (i == 0) { wg_wait<1>(); release_b(st - 2); }
        }
        fence_regs(ak); fence_regs(av);
        if (l == 0) mbar_wait(sb + B_CSRDY, 0);
        mbar_wait(sb + B_STAT + wg * 8, sph); sph ^= 1;
        const float2 s0 = lds_f2(stat_sm), s1 = lds_f2(stat_sm + 64);
        STAMP(wg, l * 24 + 2);
        const uint32_t pk_s = ring + (2 * wg) * SLOT + 16384, v_s = ring + (2 * wg + 1) * SLOT + 16384;
#pragma unroll
        for (int s = 0; s < 4; s++) {
          uint32_t pk[4], pv[4];
#pragma unroll
          for (int u = 0; u < 2; u++) {
            const int j = 2 * s + u;
            const float2 ck = lds_f2(sb + SM_CS + (64 + 8 * j + 2 * t) * 4), cv = lds_f2(sb + SM_CS + (128 + 8 * j + 2 * t) * 4);
            pk[2 * u] = pack_bf16(phi(s0.x * fmaf(s0.y, ck.x, ak[4 * j])), phi(s0.x * fmaf(s0.y, ck.y, ak[4 * j + 1])));
            pk[2 * u + 1] = pack_bf16(phi(s1.x * fmaf(s1.y, ck.x, ak[4 * j + 2])), phi(s1.x * fmaf(s1.y, ck.y, ak[4 * j + 3])));
            pv[2 * u] = pack_bf16(s0.x * fmaf(s0.y, cv.x, av[4 * j]), s0.x * fmaf(s0.y, cv.y, av[4 * j + 1]));
            pv[2 * u + 1] = pack_bf16(s1.x * fmaf(s1.y, cv.x, av[4 * j + 2]), s1.x * fmaf(s1.y, cv.y, av[4 * j + 3]));
          }
          stsm4(sw_addr(pk_s, s), pk[0], pk[1], pk[2], pk[3]);
          stsm4(sw_addr(v_s, s), pv[0], pv[1], pv[2], pv[3]);
        }
        wg_bar(wg);
        {
          float c0[4] = {0.f, 0.f, 0.f, 0.f}, c1[4] = {0.f, 0.f, 0.f, 0.f}, z0[4] = {0.f, 0.f, 0.f, 0.f}, z1[4] = {0.f, 0.f, 0.f, 0.f};
          const int m = lane >> 3;
#pragma unroll
          for (int ks = 0; ks < 4; ks++) {
            uint32_t a0, a1, a2, a3, b0, b1, b2, b3;
            const int ra = 16 * ks + 8 * (m >> 1) + (lane & 7), rb = 16 * ks + 8 * (m & 1) + (lane & 7);
            ldsm4t(v_s + ra * 128 + (((2 * wq + (m & 1)) ^ (lane & 7)) << 4), a0, a1, a2, a3);
            ldsm4t(pk_s + rb * 128 + (((2 * wq + (m >> 1)) ^ (lane & 7)) << 4), b0, b1, b2, b3);
            mma16816(c0, a0, a1, a2, a3, b0, b1);
            mma16816(c1, a0, a1, a2, a3, b2, b3);
            mma16816(z0, 0x3f803f80u, 0x3f803f80u, 0x3f803f80u, 0x3f803f80u, b0, b1);
            mma16816(z1, 0x3f803f80u, 0x3f803f80u, 0x3f803f80u, 0x3f803f80u, b2, b3);
          }
          float* kv = g_kv + (((epoch & 1) * 2 + l) * 8 + r) * 1088 + wq * 272;
          red_add_f2(kv + g * 16 + 2 * t, c0[0], c0[1]); red_add_f2(kv + (g + 8) * 16 + 2 * t, c0[2], c0[3]);
          red_add_f2(kv + g * 16 + 8 + 2 * t, c1[0], c1[1]); red_add_f2(kv + (g + 8) * 16 + 8 + 2 * t, c1[2], c1[3]);
          if (g == 0) { red_add_f2(kv + 256 + 2 * t, z0[0], z0[1]); red_add_f2(kv + 256 + 8 + 2 * t, z1[0], z1[1]); }
          signal(sb + B_KVDONE);
        }
        STAMP(wg, l * 24 + 3);
        wg_wait<2>(); release_b(st - 3);
        {
          const uint32_t bs = wait_b();
          const uint64_t da = descA(abase + 3 * 16384), db = descB(bs, 8192);
          wg_fence();
#pragma unroll
          for (int k = 0; k < 8; k++) wgmma_n64(aq, da + (k >> 2) * 512 + 2 * (k & 3), db + 128 * k, 1);
          wg_commit();
        }
        wg_wait<2>(); release_b(st - 3);
        wg_wait<1>(); release_b(st - 2);
        wg_wait<0>(); release_b(st - 1);
        fence_regs(aq);
        if (lane == 0) mbar_arrive(afree);
        STAMP(wg, l * 24 + 4);
        uint32_t pq[16];
#pragma unroll
        for (int j = 0; j < 8; j++) {
          const float2 cq = lds_f2(sb + SM_CS + (8 * j + 2 * t) * 4);
          pq[2 * j] = pack_bf16(phi(s0.x * fmaf(s0.y, cq.x, aq[4 * j])), phi(s0.x * fmaf(s0.y, cq.y, aq[4 * j + 1])));
          pq[2 * j + 1] = pack_bf16(phi(s1.x * fmaf(s1.y, cq.x, aq[4 * j + 2])), phi(s1.x * fmaf(s1.y, cq.y, aq[4 * j + 3])));
        }
        STAMP(wg, l * 24 + 5);
        mbar_wait(sb + B_KVRDY, l);
        STAMP(wg, l * 24 + 6);
#pragma unroll
        for (int hh = 0; hh < 4; hh++) {
          const uint2 f0 = lds_u2(ring + 16384 + (hh * 3 + 0) * 256 + lane * 8), f1 = lds_u2(ring + 16384 + (hh * 3 + 1) * 256 + lane * 8),
                      fz = lds_u2(ring + 16384 + (hh * 3 + 2) * 256 + lane * 8);
          float c0[4] = {0.f, 0.f, 0.f, 0.f}, c1[4] = {0.f, 0.f, 0.f, 0.f}, cz[4] = {0.f, 0.f, 0.f, 0.f};
          mma16816(cz, pq[4 * hh], pq[4 * hh + 1], pq[4 * hh + 2], pq[4 * hh + 3], fz.x, fz.y);
          mma16816(c0, pq[4 * hh], pq[4 * hh + 1], pq[4 * hh + 2], pq[4 * hh + 3], f0.x, f0.y);
          mma16816(c1, pq[4 * hh], pq[4 * hh + 1], pq[4 * hh + 2], pq[4 * hh + 3], f1.x, f1.y);
          const float i0 = rcp(cz[0] + 1e-6f), i1 = rcp(cz[2] + 1e-6f);
          stsm4(sw_addr(abase, hh), pack_bf16(c0[0] * i0, c0[1] * i0), pack_bf16(c0[2] * i1, c0[3] * i1),
                pack_bf16(c1[0] * i0, c1[1] * i0), pack_bf16(c1[2] * i1, c1[3] * i1));
        }
        fence_async_smem();
        signal(own);
        wg_bar(wg);
        STAMP(wg, l * 24 + 7);
      }
      {
        float acc[32];
        zero_regs(acc);
#pragma unroll 1
        for (int i = 0; i < 4; i++) {
          const uint32_t bs = wait_b();
          const uint64_t da = descA(abase + i * 16384), db = descB(bs, 8192);
          if (i > 0) wait_a(2 * i);
          wg_fence();
#pragma unroll
          for (int k = 0; k < 4; k++) wgmma_n64(acc, da + 2 * k, db + 128 * k, (i | k) != 0);
          wg_commit();
          wait_a(2 * i + 1);
          if (i == 0) STAMP(wg, l * 24 + 8);
          wg_fence();
#pragma unroll
          for (int k = 0; k < 4; k++) wgmma_n64(acc, da + 512 + 2 * k, db + 512 + 128 * k, 1);
          wg_commit();
          if (i > 0) { wg_wait<2>(); release_b(st - 2); }
        }
        wg_wait<0>(); release_b(st - 1);
        fence_regs(acc);
        if (lane == 0) mbar_arrive(afree);
        STAMP(wg, l * 24 + 9);
#pragma unroll
        for (int j = 0; j < 8; j++) {
          xr[2 * j] = pack_bf16(bf_lo(xr[2 * j]) + acc[4 * j], bf_hi(xr[2 * j]) + acc[4 * j + 1]);
          xr[2 * j + 1] = pack_bf16(bf_lo(xr[2 * j + 1]) + acc[4 * j + 2], bf_hi(xr[2 * j + 1]) + acc[4 * j + 3]);
        }
#pragma unroll
        for (int s = 0; s < 4; s++) stsm4(sw_addr(abase, s), xr[4 * s], xr[4 * s + 1], xr[4 * s + 2], xr[4 * s + 3]);
        fence_async_smem();
        signal(own);
        wg_bar(wg);
        STAMP(wg, l * 24 + 10);
      }
      {
        float acc[88];
        zero_regs(acc);
#pragma unroll 1
        for (int i = 0; i < 8; i++) {
          if (i > 0) wait_a(i);
          if (i == 1) STAMP(wg, l * 24 + 11);
          const uint32_t bs = wait_b();
          const uint64_t da = descA(abase + i * 8192), db = descB(bs, 8192);
          wg_fence();
#pragma unroll
          for (int k = 0; k < 4; k++) wgmma_n176(acc, da + 2 * k, db + 128 * k, (i | k) != 0);
          wg_commit();
          if (i == 0) publish_stats(xr, stat_dst + (2 * l + 1) * 32 * 512, t, tag);
          if (i > 0) { wg_wait<1>(); release_b(st - 2); }
        }
        mbar_wait(sb + B_STAT + wg * 8, sph); sph ^= 1;
        const float2 s0 = lds_f2(stat_sm), s1 = lds_f2(stat_sm + 64);
        rs0 = s0.x; rs1 = s1.x;
        wg_wait<0>(); release_b(st - 1);
        fence_regs(acc);
        if (lane == 0) mbar_arrive(afree);
        STAMP(wg, l * 24 + 12);
        const uint32_t hrow = abase + (lane >> 4) * 1024 + (2 * wq + ((lane >> 3) & 1)) * 128 + (lane & 7) * 16;
#pragma unroll
        for (int s = 0; s < 11; s++) {
          uint32_t p[4];
#pragma unroll
          for (int u = 0; u < 2; u++) {
            const int j = 2 * s + u;
            const float2 c = lds_f2(sb + SM_CS + (192 + 8 * j + 2 * t) * 4);
            p[2 * u] = pack_bf16_relu(fmaf(s0.y, c.x, acc[4 * j]), fmaf(s0.y, c.y, acc[4 * j + 1]));
            p[2 * u + 1] = pack_bf16_relu(fmaf(s1.y, c.x, acc[4 * j + 2]), fmaf(s1.y, c.y, acc[4 * j + 3]));
          }
          stsm4(hrow + s * 2048, p[0], p[1], p[2], p[3]);
          if (s == 3 || s == 7 || s == 10) { fence_async_smem(); signal(own + (s >> 2) * 8); }
        }
        wg_bar(wg);
        STAMP(wg, l * 24 + 13);
      }
      {
        float ap[32], ao[32];
        float bp[32], bo[32];
        zero_regs(ap); zero_regs(ao); zero_regs(bp); zero_regs(bo);
#pragma unroll 1
        for (int tt = 0; tt < 3; tt++) {
          const uint32_t bs = wait_b(); wait_b();
          const uint64_t db = descB(bs, SLOT);
#pragma unroll
          for (int bb = 0; bb < 3; bb++) {
            const int slot = (3 * tt + bb) & 7;
            if (tt > 0) wait_a(slot);
            if (tt == 1 && bb == 0) STAMP(wg, l * 24 + 14);
            const uint64_t da = descH(abase + slot * 8192);
            wg_fence();
#pragma unroll
            for (int k = 0; k < (bb == 2 ? 3 : 4); k++) wgmma_n128(ap, ao, da + 128 * k, db + 128 * (4 * bb + k), (tt | bb | k) != 0);
            wg_commit();
            if (bb == 0 && tt > 0) {
              wg_wait<1>(); release_b(st - 4); release_b(st - 3);
              if (lane == 0) mbar_arrive(afree + 8 * tt);
              if (tt == 2 && lane == 0) { mbar_arrive_remote(mapa(sb + B_PFREE + wg * 8, (r & 1) ^ 1)); if (wq == 0) mbar_expect_tx(sb + B_PRDY + wg * 8, 8192); }
            }
          }
        }
        {
          const uint32_t bs0 = wait_b();
          const uint64_t db = descB(bs0, SLOT);
#pragma unroll
          for (int bb = 0; bb < 3; bb++) {
            wait_a(1 + bb);
            const uint64_t da = descH(abase + (1 + bb) * 8192);
            wg_fence();
#pragma unroll
            for (int k = 0; k < (bb == 2 ? 3 : 4); k++) wgmma_n64(bp, da + 128 * k, db + 128 * (4 * bb + k), 1);
            wg_commit();
            if (bb == 0) { wg_wait<1>(); release_b(st - 3); release_b(st - 2); }
          }
          const uint32_t bs1 = wait_b();
          const uint64_t db1 = descB(bs1, SLOT), da = descH(abase + 8192);
          wg_fence();
#pragma unroll
          for (int k = 0; k < 11; k++) wgmma_n64(bo, da + (k >> 2) * 512 + 128 * (k & 3), db1 + 128 * k, 1);
          wg_commit();
          wg_wait<1>(); release_b(st - 2);
          fence_regs(ap); fence_regs(ao); fence_regs(bp);
#pragma unroll
          for (int i = 0; i < 32; i++) ap[i] += bp[i];
          STAMP(wg, l * 24 + 15);
          mbar_wait(sb + B_PFREE + wg * 8, l);
          const uint32_t rdst = mapa(abase + 4 * 8192 + (tid & 127) * 16, (r & 1) ^ 1), rbar = mapa(sb + B_PRDY + wg * 8, (r & 1) ^ 1);
#pragma unroll
          for (int i = 0; i < 4; i++)
            st_async_v4(rdst + i * 2048, pack_bf16(ap[8 * i], ap[8 * i + 1]), pack_bf16(ap[8 * i + 2], ap[8 * i + 3]),
                        pack_bf16(ap[8 * i + 4], ap[8 * i + 5]), pack_bf16(ap[8 * i + 6], ap[8 * i + 7]), rbar);
          wg_wait<0>(); release_b(st - 1);
          fence_regs(bo);
#pragma unroll
          for (int i = 0; i < 32; i++) ao[i] += bo[i];
          STAMP(wg, l * 24 + 16);
          mbar_wait(sb + B_PRDY + wg * 8, l);
          STAMP(wg, l * 24 + 17);
#pragma unroll
          for (int i = 0; i < 4; i++) {
            const uint4 p = lds_u4(abase + 4 * 8192 + i * 2048 + (tid & 127) * 16);
            xr[4 * i] = pack_bf16(fmaf(rs0, ao[8 * i] + bf_lo(p.x), bf_lo(xr[4 * i])), fmaf(rs0, ao[8 * i + 1] + bf_hi(p.x), bf_hi(xr[4 * i])));
            xr[4 * i + 1] = pack_bf16(fmaf(rs1, ao[8 * i + 2] + bf_lo(p.y), bf_lo(xr[4 * i + 1])), fmaf(rs1, ao[8 * i + 3] + bf_hi(p.y), bf_hi(xr[4 * i + 1])));
            xr[4 * i + 2] = pack_bf16(fmaf(rs0, ao[8 * i + 4] + bf_lo(p.z), bf_lo(xr[4 * i + 2])), fmaf(rs0, ao[8 * i + 5] + bf_hi(p.z), bf_hi(xr[4 * i + 2])));
            xr[4 * i + 3] = pack_bf16(fmaf(rs1, ao[8 * i + 6] + bf_lo(p.w), bf_lo(xr[4 * i + 3])), fmaf(rs1, ao[8 * i + 7] + bf_hi(p.w), bf_hi(xr[4 * i + 3])));
          }
          signal(afree);
#pragma unroll
          for (int s = 0; s < 4; s++) stsm4(sw_addr(abase, s), xr[4 * s], xr[4 * s + 1], xr[4 * s + 2], xr[4 * s + 3]);
          fence_async_smem();
          signal(own);
          wg_bar(wg);
          STAMP(wg, l * 24 + 18);
        }
      }
    }
  }
}

typedef CUresult (*EncodeFn)(CUtensorMap*, CUtensorMapDataType, cuuint32_t, void*, const cuuint64_t*, const cuuint64_t*, const cuuint32_t*,
                             const cuuint32_t*, CUtensorMapInterleave, CUtensorMapSwizzle, CUtensorMapL2promotion, CUtensorMapFloatOOBfill);

CUtensorMap make_map(EncodeFn enc, const void* ptr, uint64_t cols, uint64_t rows, uint32_t box_rows) {
  CUtensorMap m;
  cuuint64_t gd[2] = {cols, rows}, gs[1] = {cols * 2};
  cuuint32_t bd[2] = {64, box_rows}, es[2] = {1, 1};
  enc(&m, CU_TENSOR_MAP_DATA_TYPE_BFLOAT16, 2, const_cast<void*>(ptr), gd, gs, bd, es, CU_TENSOR_MAP_INTERLEAVE_NONE,
      CU_TENSOR_MAP_SWIZZLE_128B, CU_TENSOR_MAP_L2_PROMOTION_L2_128B, CU_TENSOR_MAP_FLOAT_OOB_FILL_NONE);
  return m;
}

}

extern "C" void kernel_launch(void* const* d_in, const int* in_sizes, int n_in, void* d_out, int out_size) {
  (void)in_sizes; (void)n_in; (void)out_size;
  const __nv_bfloat16* x = (const __nv_bfloat16*)d_in[0];
  const __nv_bfloat16* wqkv = (const __nv_bfloat16*)d_in[1];
  const __nv_bfloat16* wo = (const __nv_bfloat16*)d_in[2];
  const __nv_bfloat16* w1 = (const __nv_bfloat16*)d_in[4];
  const __nv_bfloat16* w2 = (const __nv_bfloat16*)d_in[5];
  void* fn = nullptr;
  cudaDriverEntryPointQueryResult q;
  cudaGetDriverEntryPoint("cuTensorMapEncodeTiled", &fn, cudaEnableDefault, &q);
  EncodeFn enc = (EncodeFn)fn;
  const CUtensorMap tm_x = make_map(enc, x, kD, kS, 64), tm_out = make_map(enc, d_out, kD, kS, 64),
                    tm_wqkv = make_map(enc, wqkv, 3 * kD, kD, 64), tm_wo = make_map(enc, wo, kD, kD, 64),
                    tm_w1 = make_map(enc, w1, kFF, kD, 64), tm_w2 = make_map(enc, w2, kD, kFF, kHS);
  cudaFuncSetAttribute(fused_kernel, cudaFuncAttributeMaxDynamicSharedMemorySize, SM_TOTAL);
  fused_kernel<<<128, 384, SM_TOTAL>>>(tm_x, tm_out, tm_wqkv, tm_wo, tm_w1, tm_w2, wqkv, wo, w1, w2);
}
```

```cpp
#include <cuda_runtime.h>
#include <cuda_bf16.h>
#include <cuda.h>
#include <stdint.h>

namespace {

constexpr int kS = 2048, kD = 512, kFF = 1376, kHS = 176;
constexpr uint32_t SM_RING = 131072, SLOT = 24576, SM_MISC = 229376;
constexpr uint32_t SM_STAT = SM_MISC;
constexpr uint32_t SM_CS = SM_MISC + 1024;
constexpr uint32_t SM_BAR = SM_CS + 1472;
constexpr uint32_t B_BFULL = SM_BAR, B_BEMPTY = SM_BAR + 32, B_AFULL = SM_BAR + 64  ,
                   B_AFREE = SM_BAR + 192  , B_OWN = SM_BAR + 240  , B_STAT = SM_BAR + 288  ,
                   B_CSRDY = SM_BAR + 304  , B_KVDONE = SM_BAR + 320, B_KVRDY = SM_BAR + 328,
                   B_PRDY = SM_BAR + 336  , B_PFREE = SM_BAR + 352  ;
constexpr uint32_t SM_TOTAL = SM_BAR + 368;
static_assert(SM_TOTAL <= 232448, "smem");
constexpr uint32_t SPIN_LIMIT = 1u << 22;

__device__ uint32_t g_epoch[128 * 8];
__device__ uint32_t g_flags[32 * 32];
__device__ uint32_t g_cnt[2 * 8 * 32];
__device__ __align__(16) float4 g_cs[8 * 2 * 16 * 48];
__device__ __align__(16) float g_kv[2 * 2 * 8 * 1088];
__device__ __align__(128) float2 g_stats[4 * 32 * 64 * 8];
__device__ __align__(1024) uint4 g_act[3 * 32 * 8 * 512];
__device__ __align__(1024) uint4 g_h[32 * 8 * 3 * 512];
#define STAMP(role, i) do {} while (0)

__device__ __forceinline__ uint32_t smem_u32(const void* p) { return (uint32_t)__cvta_generic_to_shared(p); }
__device__ __forceinline__ void mbar_init(uint32_t bar, uint32_t cnt) { asm volatile("mbarrier.init.shared::cta.b64 [%0], %1;" :: "r"(bar), "r"(cnt)); }
__device__ __forceinline__ void mbar_expect_tx(uint32_t bar, uint32_t bytes) { asm volatile("mbarrier.arrive.expect_tx.shared::cta.b64 _, [%0], %1;" :: "r"(bar), "r"(bytes) : "memory"); }
__device__ __forceinline__ void mbar_arrive(uint32_t bar) { asm volatile("mbarrier.arrive.shared::cta.b64 _, [%0];" :: "r"(bar) : "memory"); }
__device__ __forceinline__ void mbar_arrive_remote(uint32_t bar) { asm volatile("mbarrier.arrive.shared::cluster.b64 _, [%0];" :: "r"(bar) : "memory"); }
__device__ __forceinline__ void mbar_wait(uint32_t bar, uint32_t parity) {
  asm volatile("{\n.reg .pred p;\n.reg .u32 c;\nmov.u32 c, 0;\nWAIT_LOOP:\n"
               "mbarrier.try_wait.parity.shared::cta.b64 p, [%0], %1;\n@p bra WAIT_DONE;\n"
               "add.u32 c, c, 1;\nsetp.lt.u32 p, c, %2;\n@p bra WAIT_LOOP;\ntrap;\nWAIT_DONE:\n}"
               :: "r"(bar), "r"(parity), "n"(SPIN_LIMIT) : "memory");
}
__device__ __forceinline__ uint32_t mapa(uint32_t addr, uint32_t rank) { uint32_t r; asm volatile("mapa.shared::cluster.u32 %0, %1, %2;" : "=r"(r) : "r"(addr), "r"(rank)); return r; }
__device__ __forceinline__ bool elect_one() { uint32_t p; asm volatile("{\n.reg .pred P;\nelect.sync _|P, 0xffffffff;\nselp.u32 %0, 1, 0, P;\n}" : "=r"(p)); return p; }
__device__ __forceinline__ void bulk_g2s(uint32_t dst, const void* src, uint32_t bytes, uint32_t bar) {
  asm volatile("cp.async.bulk.shared::cluster.global.mbarrier::complete_tx::bytes [%0], [%1], %2, [%3];" :: "r"(dst), "l"(src), "r"(bytes), "r"(bar) : "memory");
}
__device__ __forceinline__ void bulk_s2g(void* dst, uint32_t src, uint32_t bytes) { asm volatile("cp.async.bulk.global.shared::cta.bulk_group [%0], [%1], %2;" :: "l"(dst), "r"(src), "r"(bytes) : "memory"); }
__device__ __forceinline__ void bulk_commit() { asm volatile("cp.async.bulk.commit_group;" ::: "memory"); }
template <int N> __device__ __forceinline__ void bulk_wait() { asm volatile("cp.async.bulk.wait_group %0;" :: "n"(N) : "memory"); }
__device__ __forceinline__ void tma_load(uint32_t dst, const CUtensorMap* m, int c0, int c1, uint32_t bar) {
  asm volatile("cp.async.bulk.tensor.2d.shared::cluster.global.mbarrier::complete_tx::bytes [%0], [%1, {%3, %4}], [%2];" :: "r"(dst), "l"(m), "r"(bar), "r"(c0), "r"(c1) : "memory");
}
__device__ __forceinline__ void tma_store(const CUtensorMap* m, uint32_t src, int c0, int c1) {
  asm volatile("cp.async.bulk.tensor.2d.global.shared::cta.bulk_group [%0, {%2, %3}], [%1];" :: "l"(m), "r"(src), "r"(c0), "r"(c1) : "memory");
}
__device__ __forceinline__ void prefetch_l2(const void* p, uint32_t bytes) { asm volatile("cp.async.bulk.prefetch.L2.global [%0], %1;" :: "l"(p), "r"(bytes) : "memory"); }
__device__ __forceinline__ void prefetch_map(const CUtensorMap* m) { asm volatile("prefetch.tensormap [%0];" :: "l"(m) : "memory"); }
__device__ __forceinline__ void fence_async_smem() { asm volatile("fence.proxy.async.shared::cta;" ::: "memory"); }
__device__ __forceinline__ void fence_async_global() { asm volatile("fence.proxy.async.global;" ::: "memory"); }
__device__ __forceinline__ void fence_gpu() { asm volatile("fence.acq_rel.gpu;" ::: "memory"); }
__device__ __forceinline__ void st_release(uint32_t* p, uint32_t v) { asm volatile("st.release.gpu.global.u32 [%0], %1;" :: "l"(p), "r"(v) : "memory"); }
__device__ __forceinline__ uint32_t ld_acquire(const uint32_t* p) { uint32_t v; asm volatile("ld.acquire.gpu.global.u32 %0, [%1];" : "=r"(v) : "l"(p) : "memory"); return v; }
__device__ __forceinline__ uint32_t ld_relaxed(const uint32_t* p) { uint32_t v; asm volatile("ld.relaxed.gpu.global.u32 %0, [%1];" : "=r"(v) : "l"(p) : "memory"); return v; }
__device__ __forceinline__ float2 ld_relaxed_f2(const void* p) { float2 v; asm volatile("ld.relaxed.gpu.global.v2.f32 {%0,%1}, [%2];" : "=f"(v.x), "=f"(v.y) : "l"(p) : "memory"); return v; }
__device__ __forceinline__ float4 ld_relaxed_f4(const void* p) { float4 v; asm volatile("ld.relaxed.gpu.global.v4.f32 {%0,%1,%2,%3}, [%4];" : "=f"(v.x), "=f"(v.y), "=f"(v.z), "=f"(v.w) : "l"(p) : "memory"); return v; }
__device__ __forceinline__ void st_relaxed_b64(void* p, float a, uint32_t b) {
  asm volatile("{\n.reg .b64 v;\nmov.b64 v, {%1, %2};\nst.relaxed.gpu.global.b64 [%0], v;\n}" :: "l"(p), "r"(__float_as_uint(a)), "r"(b) : "memory");
}
__device__ __forceinline__ void red_add_u32(uint32_t* p, uint32_t v) { asm volatile("red.relaxed.gpu.global.add.u32 [%0], %1;" :: "l"(p), "r"(v) : "memory"); }
__device__ __forceinline__ void red_add_f2(float* p, float a, float b) { asm volatile("red.relaxed.gpu.global.add.v2.f32 [%0], {%1, %2};" :: "l"(p), "f"(a), "f"(b) : "memory"); }
__device__ __forceinline__ void red_add_f4(float* p, float a, float b, float c, float d) { asm volatile("red.relaxed.gpu.global.add.v4.f32 [%0], {%1, %2, %3, %4};" :: "l"(p), "f"(a), "f"(b), "f"(c), "f"(d) : "memory"); }
__device__ __forceinline__ void st_async_v4(uint32_t dst, uint32_t a, uint32_t b, uint32_t c, uint32_t d, uint32_t bar) {
  asm volatile("st.async.weak.shared::cluster.mbarrier::complete_tx::bytes.v4.b32 [%0], {%1,%2,%3,%4}, [%5];" :: "r"(dst), "r"(a), "r"(b), "r"(c), "r"(d), "r"(bar) : "memory");
}
__device__ __forceinline__ void stsm4(uint32_t addr, uint32_t a, uint32_t b, uint32_t c, uint32_t d) {
  asm volatile("stmatrix.sync.aligned.m8n8.x4.shared.b16 [%0], {%1,%2,%3,%4};" :: "r"(addr), "r"(a), "r"(b), "r"(c), "r"(d) : "memory");
}
__device__ __forceinline__ void ldsm4(uint32_t addr, uint32_t& a, uint32_t& b, uint32_t& c, uint32_t& d) {
  asm volatile("ldmatrix.sync.aligned.m8n8.x4.shared.b16 {%0,%1,%2,%3}, [%4];" : "=r"(a), "=r"(b), "=r"(c), "=r"(d) : "r"(addr) : "memory");
}
__device__ __forceinline__ void ldsm4t(uint32_t addr, uint32_t& a, uint32_t& b, uint32_t& c, uint32_t& d) {
  asm volatile("ldmatrix.sync.aligned.m8n8.x4.trans.shared.b16 {%0,%1,%2,%3}, [%4];" : "=r"(a), "=r"(b), "=r"(c), "=r"(d) : "r"(addr) : "memory");
}
__device__ __forceinline__ float2 lds_f2(uint32_t addr) { float2 v; asm volatile("ld.shared.v2.f32 {%0,%1}, [%2];" : "=f"(v.x), "=f"(v.y) : "r"(addr) : "memory"); return v; }
__device__ __forceinline__ uint32_t lds_u32(uint32_t addr) { uint32_t v; asm volatile("ld.shared.u32 %0, [%1];" : "=r"(v) : "r"(addr) : "memory"); return v; }
__device__ __forceinline__ void sts_u4(uint32_t addr, uint4 v) { asm volatile("st.shared.v4.u32 [%0], {%1,%2,%3,%4};" :: "r"(addr), "r"(v.x), "r"(v.y), "r"(v.z), "r"(v.w) : "memory"); }
__device__ __forceinline__ uint4 ld_relaxed_u4(const void* p) { uint4 v; asm volatile("ld.relaxed.gpu.global.v4.u32 {%0,%1,%2,%3}, [%4];" : "=r"(v.x), "=r"(v.y), "=r"(v.z), "=r"(v.w) : "l"(p) : "memory"); return v; }
__device__ __forceinline__ void st_relaxed_u32(uint32_t* p, uint32_t v) { asm volatile("st.relaxed.gpu.global.u32 [%0], %1;" :: "l"(p), "r"(v) : "memory"); }
__device__ __forceinline__ void st_relaxed_f4(void* p, float a, float b, float c, uint32_t d) { asm volatile("st.relaxed.gpu.global.v4.b32 [%0], {%1,%2,%3,%4};" :: "l"(p), "r"(__float_as_uint(a)), "r"(__float_as_uint(b)), "r"(__float_as_uint(c)), "r"(d) : "memory"); }
__device__ __forceinline__ uint2 lds_u2(uint32_t addr) { uint2 v; asm volatile("ld.shared.v2.u32 {%0,%1}, [%2];" : "=r"(v.x), "=r"(v.y) : "r"(addr) : "memory"); return v; }
__device__ __forceinline__ uint4 lds_u4(uint32_t addr) { uint4 v; asm volatile("ld.shared.v4.u32 {%0,%1,%2,%3}, [%4];" : "=r"(v.x), "=r"(v.y), "=r"(v.z), "=r"(v.w) : "r"(addr) : "memory"); return v; }
__device__ __forceinline__ void sts_f2(uint32_t addr, float a, float b) { asm volatile("st.shared.v2.f32 [%0], {%1,%2};" :: "r"(addr), "f"(a), "f"(b) : "memory"); }
__device__ __forceinline__ void sts_u2(uint32_t addr, uint32_t a, uint32_t b) { asm volatile("st.shared.v2.u32 [%0], {%1,%2};" :: "r"(addr), "r"(a), "r"(b) : "memory"); }
__device__ __forceinline__ void sts_f4(uint32_t addr, float4 v) { asm volatile("st.shared.v4.f32 [%0], {%1,%2,%3,%4};" :: "r"(addr), "f"(v.x), "f"(v.y), "f"(v.z), "f"(v.w) : "memory"); }
__device__ __forceinline__ void mma16816(float (&c)[4], uint32_t a0, uint32_t a1, uint32_t a2, uint32_t a3, uint32_t b0, uint32_t b1) {
  asm volatile("mma.sync.aligned.m16n8k16.row.col.f32.bf16.bf16.f32 {%0,%1,%2,%3}, {%4,%5,%6,%7}, {%8,%9}, {%0,%1,%2,%3};"
               : "+f"(c[0]), "+f"(c[1]), "+f"(c[2]), "+f"(c[3]) : "r"(a0), "r"(a1), "r"(a2), "r"(a3), "r"(b0), "r"(b1));
}
__device__ __forceinline__ uint32_t pack_bf16(float lo, float hi) { uint32_t r; asm("cvt.rn.bf16x2.f32 %0, %1, %2;" : "=r"(r) : "f"(hi), "f"(lo)); return r; }
__device__ __forceinline__ uint32_t pack_bf16_relu(float lo, float hi) { uint32_t r; asm("cvt.rn.relu.bf16x2.f32 %0, %1, %2;" : "=r"(r) : "f"(hi), "f"(lo)); return r; }
__device__ __forceinline__ float bf_lo(uint32_t v) { return __uint_as_float(v << 16); }
__device__ __forceinline__ float bf_hi(uint32_t v) { return __uint_as_float(v & 0xffff0000u); }
__device__ __forceinline__ float ex2(float x) { float y; asm("ex2.approx.ftz.f32 %0, %1;" : "=f"(y) : "f"(x)); return y; }
__device__ __forceinline__ float rcp(float x) { float y; asm("rcp.approx.ftz.f32 %0, %1;" : "=f"(y) : "f"(x)); return y; }
__device__ __forceinline__ float phi_y(float y) { return fmaf(fmaxf(y, 1.4426950408889634e-6f), 0.6931471805599453f, ex2(fminf(y, 0.f))); }
__device__ __forceinline__ void wg_fence() { asm volatile("wgmma.fence.sync.aligned;" ::: "memory"); }
__device__ __forceinline__ void wg_commit() { asm volatile("wgmma.commit_group.sync.aligned;" ::: "memory"); }
template <int N> __device__ __forceinline__ void wg_wait() { asm volatile("wgmma.wait_group.sync.aligned %0;" :: "n"(N) : "memory"); }
template <int N> __device__ __forceinline__ void fence_regs(float (&d)[N]) {
#pragma unroll
  for (int i = 0; i < N; i++) asm volatile("" : "+f"(d[i]) :: "memory");
}
template <int N> __device__ __forceinline__ void zero_regs(float (&d)[N]) {
#pragma unroll
  for (int i = 0; i < N; i++) d[i] = 0.f;
  fence_regs(d);
}
__device__ __forceinline__ void wg_bar(int wg) { if (wg == 0) asm volatile("bar.sync 1, 128;" ::: "memory"); else asm volatile("bar.sync 2, 128;" ::: "memory"); }
__device__ __forceinline__ uint64_t mk_desc(uint32_t addr, uint32_t lbo, uint32_t sbo, uint32_t swz) {
  return (uint64_t)((addr & 0x3FFFF) >> 4) | ((uint64_t)(lbo >> 4) << 16) | ((uint64_t)(sbo >> 4) << 32) | ((uint64_t)swz << 62);
}
__device__ __forceinline__ uint64_t descA(uint32_t addr) { return mk_desc(addr, 16, 1024, 1); }
__device__ __forceinline__ uint64_t descH(uint32_t addr) { return mk_desc(addr, 1024, 128, 0); }
__device__ __forceinline__ uint64_t descB(uint32_t addr, uint32_t lbo) { return mk_desc(addr, lbo, 1024, 1); }

__device__ __forceinline__ void wgmma_n64_init(float (&d)[32], uint64_t da, uint64_t db) {
  asm volatile("{\n.reg .pred p;\nsetp.ne.b32 p, 0, 0;\n"
    "wgmma.mma_async.sync.aligned.m64n64k16.f32.bf16.bf16 "
    "{%0, %1, %2, %3, %4, %5, %6, %7, %8, %9, %10, %11, %12, %13, %14, %15, "
    "%16, %17, %18, %19, %20, %21, %22, %23, %24, %25, %26, %27, %28, %29, %30, %31}, "
    "%32, %33, p, 1, 1, 0, 1;\n}"
    : "=f"(d[0]), "=f"(d[1]), "=f"(d[2]), "=f"(d[3]), "=f"(d[4]), "=f"(d[5]), "=f"(d[6]), "=f"(d[7]),
      "=f"(d[8]), "=f"(d[9]), "=f"(d[10]), "=f"(d[11]), "=f"(d[12]), "=f"(d[13]), "=f"(d[14]), "=f"(d[15]),
      "=f"(d[16]), "=f"(d[17]), "=f"(d[18]), "=f"(d[19]), "=f"(d[20]), "=f"(d[21]), "=f"(d[22]), "=f"(d[23]),
      "=f"(d[24]), "=f"(d[25]), "=f"(d[26]), "=f"(d[27]), "=f"(d[28]), "=f"(d[29]), "=f"(d[30]), "=f"(d[31])
    : "l"(da), "l"(db));
}
__device__ __forceinline__ void wgmma_n128_init(float (&d)[32], float (&e)[32], uint64_t da, uint64_t db) {
  asm volatile("{\n.reg .pred p;\nsetp.ne.b32 p, 0, 0;\n"
    "wgmma.mma_async.sync.aligned.m64n128k16.f32.bf16.bf16 "
    "{%0, %1, %2, %3, %4, %5, %6, %7, %8, %9, %10, %11, %12, %13, %14, %15, "
    "%16, %17, %18, %19, %20, %21, %22, %23, %24, %25, %26, %27, %28, %29, %30, %31, "
    "%32, %33, %34, %35, %36, %37, %38, %39, %40, %41, %42, %43, %44, %45, %46, %47, "
    "%48, %49, %50, %51, %52, %53, %54, %55, %56, %57, %58, %59, %60, %61, %62, %63}, "
    "%64, %65, p, 1, 1, 0, 1;\n}"
    : "=f"(d[0]), "=f"(d[1]), "=f"(d[2]), "=f"(d[3]), "=f"(d[4]), "=f"(d[5]), "=f"(d[6]), "=f"(d[7]),
      "=f"(d[8]), "=f"(d[9]), "=f"(d[10]), "=f"(d[11]), "=f"(d[12]), "=f"(d[13]), "=f"(d[14]), "=f"(d[15]),
      "=f"(d[16]), "=f"(d[17]), "=f"(d[18]), "=f"(d[19]), "=f"(d[20]), "=f"(d[21]), "=f"(d[22]), "=f"(d[23]),
      "=f"(d[24]), "=f"(d[25]), "=f"(d[26]), "=f"(d[27]), "=f"(d[28]), "=f"(d[29]), "=f"(d[30]), "=f"(d[31]),
      "=f"(e[0]), "=f"(e[1]), "=f"(e[2]), "=f"(e[3]), "=f"(e[4]), "=f"(e[5]), "=f"(e[6]), "=f"(e[7]),
      "=f"(e[8]), "=f"(e[9]), "=f"(e[10]), "=f"(e[11]), "=f"(e[12]), "=f"(e[13]), "=f"(e[14]), "=f"(e[15]),
      "=f"(e[16]), "=f"(e[17]), "=f"(e[18]), "=f"(e[19]), "=f"(e[20]), "=f"(e[21]), "=f"(e[22]), "=f"(e[23]),
      "=f"(e[24]), "=f"(e[25]), "=f"(e[26]), "=f"(e[27]), "=f"(e[28]), "=f"(e[29]), "=f"(e[30]), "=f"(e[31])
    : "l"(da), "l"(db));
}
__device__ __forceinline__ void wgmma_n176_init(float (&d)[88], uint64_t da, uint64_t db) {
  asm volatile("{\n.reg .pred p;\nsetp.ne.b32 p, 0, 0;\n"
    "wgmma.mma_async.sync.aligned.m64n176k16.f32.bf16.bf16 "
    "{%0, %1, %2, %3, %4, %5, %6, %7, %8, %9, %10, %11, %12, %13, %14, %15, "
    "%16, %17, %18, %19, %20, %21, %22, %23, %24, %25, %26, %27, %28, %29, %30, %31, "
    "%32, %33, %34, %35, %36, %37, %38, %39, %40, %41, %42, %43, %44, %45, %46, %47, "
    "%48, %49, %50, %51, %52, %53, %54, %55, %56, %57, %58, %59, %60, %61, %62, %63, "
    "%64, %65, %66, %67, %68, %69, %70, %71, %72, %73, %74, %75, %76, %77, %78, %79, "
    "%80, %81, %82, %83, %84, %85, %86, %87}, "
    "%88, %89, p, 1, 1, 0, 1;\n}"
    : "=f"(d[0]), "=f"(d[1]), "=f"(d[2]), "=f"(d[3]), "=f"(d[4]), "=f"(d[5]), "=f"(d[6]), "=f"(d[7]),
      "=f"(d[8]), "=f"(d[9]), "=f"(d[10]), "=f"(d[11]), "=f"(d[12]), "=f"(d[13]), "=f"(d[14]), "=f"(d[15]),
      "=f"(d[16]), "=f"(d[17]), "=f"(d[18]), "=f"(d[19]), "=f"(d[20]), "=f"(d[21]), "=f"(d[22]), "=f"(d[23]),
      "=f"(d[24]), "=f"(d[25]), "=f"(d[26]), "=f"(d[27]), "=f"(d[28]), "=f"(d[29]), "=f"(d[30]), "=f"(d[31]),
      "=f"(d[32]), "=f"(d[33]), "=f"(d[34]), "=f"(d[35]), "=f"(d[36]), "=f"(d[37]), "=f"(d[38]), "=f"(d[39]),
      "=f"(d[40]), "=f"(d[41]), "=f"(d[42]), "=f"(d[43]), "=f"(d[44]), "=f"(d[45]), "=f"(d[46]), "=f"(d[47]),
      "=f"(d[48]), "=f"(d[49]), "=f"(d[50]), "=f"(d[51]), "=f"(d[52]), "=f"(d[53]), "=f"(d[54]), "=f"(d[55]),
      "=f"(d[56]), "=f"(d[57]), "=f"(d[58]), "=f"(d[59]), "=f"(d[60]), "=f"(d[61]), "=f"(d[62]), "=f"(d[63]),
      "=f"(d[64]), "=f"(d[65]), "=f"(d[66]), "=f"(d[67]), "=f"(d[68]), "=f"(d[69]), "=f"(d[70]), "=f"(d[71]),
      "=f"(d[72]), "=f"(d[73]), "=f"(d[74]), "=f"(d[75]), "=f"(d[76]), "=f"(d[77]), "=f"(d[78]), "=f"(d[79]),
      "=f"(d[80]), "=f"(d[81]), "=f"(d[82]), "=f"(d[83]), "=f"(d[84]), "=f"(d[85]), "=f"(d[86]), "=f"(d[87])
    : "l"(da), "l"(db));
}
__device__ __forceinline__ void wgmma_n64(float (&d)[32], uint64_t da, uint64_t db, int scale_d) {
  asm volatile("{\n.reg .pred p;\nsetp.ne.b32 p, %34, 0;\n"
    "wgmma.mma_async.sync.aligned.m64n64k16.f32.bf16.bf16 "
    "{%0, %1, %2, %3, %4, %5, %6, %7, %8, %9, %10, %11, %12, %13, %14, %15, "
    "%16, %17, %18, %19, %20, %21, %22, %23, %24, %25, %26, %27, %28, %29, %30, %31}, "
    "%32, %33, p, 1, 1, 0, 1;\n}"
    : "+f"(d[0]), "+f"(d[1]), "+f"(d[2]), "+f"(d[3]), "+f"(d[4]), "+f"(d[5]), "+f"(d[6]), "+f"(d[7]),
      "+f"(d[8]), "+f"(d[9]), "+f"(d[10]), "+f"(d[11]), "+f"(d[12]), "+f"(d[13]), "+f"(d[14]), "+f"(d[15]),
      "+f"(d[16]), "+f"(d[17]), "+f"(d[18]), "+f"(d[19]), "+f"(d[20]), "+f"(d[21]), "+f"(d[22]), "+f"(d[23]),
      "+f"(d[24]), "+f"(d[25]), "+f"(d[26]), "+f"(d[27]), "+f"(d[28]), "+f"(d[29]), "+f"(d[30]), "+f"(d[31])
    : "l"(da), "l"(db), "r"(scale_d));
}
__device__ __forceinline__ void wgmma_n128(float (&d)[32], float (&e)[32], uint64_t da, uint64_t db, int scale_d) {
  asm volatile("{\n.reg .pred p;\nsetp.ne.b32 p, %66, 0;\n"
    "wgmma.mma_async.sync.aligned.m64n128k16.f32.bf16.bf16 "
    "{%0, %1, %2, %3, %4, %5, %6, %7, %8, %9, %10, %11, %12, %13, %14, %15, "
    "%16, %17, %18, %19, %20, %21, %22, %23, %24, %25, %26, %27, %28, %29, %30, %31, "
    "%32, %33, %34, %35, %36, %37, %38, %39, %40, %41, %42, %43, %44, %45, %46, %47, "
    "%48, %49, %50, %51, %52, %53, %54, %55, %56, %57, %58, %59, %60, %61, %62, %63}, "
    "%64, %65, p, 1, 1, 0, 1;\n}"
    : "+f"(d[0]), "+f"(d[1]), "+f"(d[2]), "+f"(d[3]), "+f"(d[4]), "+f"(d[5]), "+f"(d[6]), "+f"(d[7]),
      "+f"(d[8]), "+f"(d[9]), "+f"(d[10]), "+f"(d[11]), "+f"(d[12]), "+f"(d[13]), "+f"(d[14]), "+f"(d[15]),
      "+f"(d[16]), "+f"(d[17]), "+f"(d[18]), "+f"(d[19]), "+f"(d[20]), "+f"(d[21]), "+f"(d[22]), "+f"(d[23]),
      "+f"(d[24]), "+f"(d[25]), "+f"(d[26]), "+f"(d[27]), "+f"(d[28]), "+f"(d[29]), "+f"(d[30]), "+f"(d[31]),
      "+f"(e[0]), "+f"(e[1]), "+f"(e[2]), "+f"(e[3]), "+f"(e[4]), "+f"(e[5]), "+f"(e[6]), "+f"(e[7]),
      "+f"(e[8]), "+f"(e[9]), "+f"(e[10]), "+f"(e[11]), "+f"(e[12]), "+f"(e[13]), "+f"(e[14]), "+f"(e[15]),
      "+f"(e[16]), "+f"(e[17]), "+f"(e[18]), "+f"(e[19]), "+f"(e[20]), "+f"(e[21]), "+f"(e[22]), "+f"(e[23]),
      "+f"(e[24]), "+f"(e[25]), "+f"(e[26]), "+f"(e[27]), "+f"(e[28]), "+f"(e[29]), "+f"(e[30]), "+f"(e[31])
    : "l"(da), "l"(db), "r"(scale_d));
}
__device__ __forceinline__ void wgmma_n176(float (&d)[88], uint64_t da, uint64_t db, int scale_d) {
  asm volatile("{\n.reg .pred p;\nsetp.ne.b32 p, %90, 0;\n"
    "wgmma.mma_async.sync.aligned.m64n176k16.f32.bf16.bf16 "
    "{%0, %1, %2, %3, %4, %5, %6, %7, %8, %9, %10, %11, %12, %13, %14, %15, "
    "%16, %17, %18, %19, %20, %21, %22, %23, %24, %25, %26, %27, %28, %29, %30, %31, "
    "%32, %33, %34, %35, %36, %37, %38, %39, %40, %41, %42, %43, %44, %45, %46, %47, "
    "%48, %49, %50, %51, %52, %53, %54, %55, %56, %57, %58, %59, %60, %61, %62, %63, "
    "%64, %65, %66, %67, %68, %69, %70, %71, %72, %73, %74, %75, %76, %77, %78, %79, "
    "%80, %81, %82, %83, %84, %85, %86, %87}, "
    "%88, %89, p, 1, 1, 0, 1;\n}"
    : "+f"(d[0]), "+f"(d[1]), "+f"(d[2]), "+f"(d[3]), "+f"(d[4]), "+f"(d[5]), "+f"(d[6]), "+f"(d[7]),
      "+f"(d[8]), "+f"(d[9]), "+f"(d[10]), "+f"(d[11]), "+f"(d[12]), "+f"(d[13]), "+f"(d[14]), "+f"(d[15]),
      "+f"(d[16]), "+f"(d[17]), "+f"(d[18]), "+f"(d[19]), "+f"(d[20]), "+f"(d[21]), "+f"(d[22]), "+f"(d[23]),
      "+f"(d[24]), "+f"(d[25]), "+f"(d[26]), "+f"(d[27]), "+f"(d[28]), "+f"(d[29]), "+f"(d[30]), "+f"(d[31]),
      "+f"(d[32]), "+f"(d[33]), "+f"(d[34]), "+f"(d[35]), "+f"(d[36]), "+f"(d[37]), "+f"(d[38]), "+f"(d[39]),
      "+f"(d[40]), "+f"(d[41]), "+f"(d[42]), "+f"(d[43]), "+f"(d[44]), "+f"(d[45]), "+f"(d[46]), "+f"(d[47]),
      "+f"(d[48]), "+f"(d[49]), "+f"(d[50]), "+f"(d[51]), "+f"(d[52]), "+f"(d[53]), "+f"(d[54]), "+f"(d[55]),
      "+f"(d[56]), "+f"(d[57]), "+f"(d[58]), "+f"(d[59]), "+f"(d[60]), "+f"(d[61]), "+f"(d[62]), "+f"(d[63]),
      "+f"(d[64]), "+f"(d[65]), "+f"(d[66]), "+f"(d[67]), "+f"(d[68]), "+f"(d[69]), "+f"(d[70]), "+f"(d[71]),
      "+f"(d[72]), "+f"(d[73]), "+f"(d[74]), "+f"(d[75]), "+f"(d[76]), "+f"(d[77]), "+f"(d[78]), "+f"(d[79]),
      "+f"(d[80]), "+f"(d[81]), "+f"(d[82]), "+f"(d[83]), "+f"(d[84]), "+f"(d[85]), "+f"(d[86]), "+f"(d[87])
    : "l"(da), "l"(db), "r"(scale_d));
}

__device__ __forceinline__ void publish_stats(const uint32_t (&xr)[16], float2* dst  , int t, uint32_t tag) {
  float s0 = 0.f, s1 = 0.f;
#pragma unroll
  for (int j = 0; j < 8; j++) { s0 += bf_lo(xr[2 * j]) + bf_hi(xr[2 * j]); s1 += bf_lo(xr[2 * j + 1]) + bf_hi(xr[2 * j + 1]); }
  s0 += __shfl_xor_sync(0xffffffff, s0, 1); s1 += __shfl_xor_sync(0xffffffff, s1, 1);
  s0 += __shfl_xor_sync(0xffffffff, s0, 2); s1 += __shfl_xor_sync(0xffffffff, s1, 2);
  const float m0 = s0 * (1.f / 64.f), m1 = s1 * (1.f / 64.f);
  float q0 = 0.f, q1 = 0.f;
#pragma unroll
  for (int j = 0; j < 8; j++) {
    float a = bf_lo(xr[2 * j]) - m0, b = bf_hi(xr[2 * j]) - m0, c = bf_lo(xr[2 * j + 1]) - m1, d = bf_hi(xr[2 * j + 1]) - m1;
    q0 = fmaf(a, a, q0); q0 = fmaf(b, b, q0); q1 = fmaf(c, c, q1); q1 = fmaf(d, d, q1);
  }
  q0 += __shfl_xor_sync(0xffffffff, q0, 1); q1 += __shfl_xor_sync(0xffffffff, q1, 1);
  q0 += __shfl_xor_sync(0xffffffff, q0, 2); q1 += __shfl_xor_sync(0xffffffff, q1, 2);
  if (t == 0) {
    st_relaxed_b64(dst, s0, (__float_as_uint(q0) & ~1u) | tag);
    st_relaxed_b64(dst + 64, s1, (__float_as_uint(q1) & ~1u) | tag);
  }
}

__device__ __forceinline__ float2 finish_stats(const float4& v0, const float4& v1, const float4& v2, const float4& v3) {
  const float mean = (v0.x + v0.z + v1.x + v1.z + v2.x + v2.z + v3.x + v3.z) * (1.f / 512.f);
  float m2 = v0.y + v0.w + v1.y + v1.w + v2.y + v2.w + v3.y + v3.w;
  float d, b = 0.f;
  d = v0.x * (1.f / 64.f) - mean; b = fmaf(d, d, b); d = v0.z * (1.f / 64.f) - mean; b = fmaf(d, d, b);
  d = v1.x * (1.f / 64.f) - mean; b = fmaf(d, d, b); d = v1.z * (1.f / 64.f) - mean; b = fmaf(d, d, b);
  d = v2.x * (1.f / 64.f) - mean; b = fmaf(d, d, b); d = v2.z * (1.f / 64.f) - mean; b = fmaf(d, d, b);
  d = v3.x * (1.f / 64.f) - mean; b = fmaf(d, d, b); d = v3.z * (1.f / 64.f) - mean; b = fmaf(d, d, b);
  m2 = fmaf(b, 64.f, m2);
  return make_float2(rsqrtf(m2 * (1.f / 512.f) + 1e-5f), -mean);
}
__device__ __forceinline__ uint32_t tag_yw(const float4& v) { return __float_as_uint(v.y) & __float_as_uint(v.w); }
__device__ __forceinline__ uint32_t tag_yw_or(const float4& v) { return __float_as_uint(v.y) | __float_as_uint(v.w); }
__device__ __forceinline__ void gather_stats(const float2* src  , uint32_t sm_dst, uint32_t bar, int lane, uint32_t tag) {
  const float2* p = src + lane * 8;
  float4 v[8];
  uint32_t cnt = 0;
  while (true) {
#pragma unroll
    for (int i = 0; i < 8; i++) v[i] = ld_relaxed_f4(p + (i >> 2) * 256 + (i & 3) * 2);
    uint32_t a = 0xffffffffu, o = 0;
#pragma unroll
    for (int i = 0; i < 8; i++) { a &= tag_yw(v[i]); o |= tag_yw_or(v[i]); }
    if (__all_sync(0xffffffff, ((tag ? ~a : o) & 1u) == 0)) break;
    if (++cnt > SPIN_LIMIT) __trap();
  }
  const float2 r0 = finish_stats(v[0], v[1], v[2], v[3]), r1 = finish_stats(v[4], v[5], v[6], v[7]);
  sts_f2(sm_dst + lane * 8, r0.x, r0.y);
  sts_f2(sm_dst + (32 + lane) * 8, r1.x, r1.y);
  __syncwarp();
  if (lane == 0) mbar_arrive(bar);
}

__device__ __forceinline__ void colsum_task(const __nv_bfloat16* p  , int pitch, bool ok, int row0, float4* dst  , int lane, uint32_t tag) {
  const int rg = lane >> 3;
  float a[8];
#pragma unroll
  for (int i = 0; i < 8; i++) a[i] = 0.f;
  if (ok) {
    uint4 v[8];
#pragma unroll
    for (int i = 0; i < 8; i++) v[i] = __ldg((const uint4*)(p + (size_t)(row0 + 4 * i + rg) * pitch));
#pragma unroll
    for (int i = 0; i < 8; i++) {
      a[0] += bf_lo(v[i].x); a[1] += bf_hi(v[i].x); a[2] += bf_lo(v[i].y); a[3] += bf_hi(v[i].y);
      a[4] += bf_lo(v[i].z); a[5] += bf_hi(v[i].z); a[6] += bf_lo(v[i].w); a[7] += bf_hi(v[i].w);
    }
  }
#pragma unroll
  for (int i = 0; i < 8; i++) { a[i] += __shfl_xor_sync(0xffffffff, a[i], 8); a[i] += __shfl_xor_sync(0xffffffff, a[i], 16); }
  if (rg == 0) {
    st_relaxed_f4(dst, a[0], a[1], a[2], (__float_as_uint(a[3]) & ~1u) | tag);
    st_relaxed_f4(dst + 1, a[4], a[5], a[6], (__float_as_uint(a[7]) & ~1u) | tag);
  }
}
__device__ __forceinline__ void colsum_gather(const float4* src, uint32_t sm_dst, int nunits, uint32_t bar, int lane, uint32_t tag) {
#pragma unroll 1
  for (int j = 0; j < 3; j++) {
    const float4* p = src + (lane >> 4) * 8 * 48 + j * 16 + (lane & 15);
    float4 v[8];
    uint32_t cnt = 0;
    while (true) {
      uint32_t bad = 0;
#pragma unroll
      for (int i = 0; i < 8; i++) v[i] = ld_relaxed_f4(p + i * 48);
#pragma unroll
      for (int i = 0; i < 8; i++) bad |= __float_as_uint(v[i].w) ^ tag;
      if (__all_sync(0xffffffff, (bad & 1u) == 0)) break;
      if (++cnt > SPIN_LIMIT) __trap();
    }
    float4 a = v[0];
#pragma unroll
    for (int i = 1; i < 8; i++) { a.x += v[i].x; a.y += v[i].y; a.z += v[i].z; a.w += v[i].w; }
    a.x += __shfl_xor_sync(0xffffffff, a.x, 16); a.y += __shfl_xor_sync(0xffffffff, a.y, 16);
    a.z += __shfl_xor_sync(0xffffffff, a.z, 16); a.w += __shfl_xor_sync(0xffffffff, a.w, 16);
    if (lane < 16 && j * 16 + lane < nunits) sts_f4(sm_dst + (j * 16 + lane) * 16, a);
  }
  __syncwarp();
  if (lane == 0) mbar_arrive(bar);
}

__device__ __forceinline__ void wait_flag_acq(const uint32_t* f, uint32_t ev) {
  uint32_t cnt = 0;
  while ((int32_t)(ld_acquire(f) - ev) < 0) { if (++cnt > SPIN_LIMIT) __trap(); }
}
__device__ __forceinline__ void wait_flags(const uint32_t* f  , uint32_t ev) {
  uint32_t cnt = 0;
  while (!__all_sync(0xffffffff, (int32_t)(ld_relaxed(f) - ev) >= 0)) { if (++cnt > SPIN_LIMIT) __trap(); }
}
__device__ __forceinline__ void publish_chunk(uint4* gdst, uint32_t src, uint32_t* flag, uint32_t ev, int lane) {
  if (lane == 0) { bulk_s2g(gdst, src, 8192); bulk_commit(); bulk_wait<0>(); st_relaxed_u32(flag, ev); }
  __syncwarp();
}
__device__ __forceinline__ void fetch_chunks(const uint4* gbuf  , const uint32_t* flags, uint32_t abase, uint32_t afull, int r, uint32_t ev, int lane) {
  wait_flags(flags + (lane & 7), ev);
  if (elect_one()) {
#pragma unroll
    for (int i = 1; i < 8; i++) {
      mbar_expect_tx(afull + i * 8, 8192);
      bulk_g2s(abase + i * 8192, gbuf + ((r + i) & 7) * 512, 8192, afull + i * 8);
    }
  }
  __syncwarp();
}

__global__ void __cluster_dims__(2, 1, 1) __launch_bounds__(384, 1)
fused_kernel(const __grid_constant__ CUtensorMap tm_x, const __grid_constant__ CUtensorMap tm_out,
             const __grid_constant__ CUtensorMap tm_wqkv, const __grid_constant__ CUtensorMap tm_wo,
             const __grid_constant__ CUtensorMap tm_w1, const __grid_constant__ CUtensorMap tm_w2,
             const __nv_bfloat16* __restrict__ wqkv, const __nv_bfloat16* __restrict__ wo,
             const __nv_bfloat16* __restrict__ w1, const __nv_bfloat16* __restrict__ w2) {
  extern __shared__ __align__(1024) uint8_t smem_raw[];
  const uint32_t sb = smem_u32(smem_raw);
  const int tid = threadIdx.x, lane = tid & 31;
  const int warp = __shfl_sync(0xffffffff, tid >> 5, 0);
  const int bid = blockIdx.x, cb = bid >> 3, r = bid & 7;

  if (tid == 0) {
    if (sb & 1023) __trap();
    for (int i = 0; i < 4; i++) { mbar_init(sb + B_BFULL + i * 8, 1); mbar_init(sb + B_BEMPTY + i * 8, 8); }
    for (int i = 0; i < 16; i++) mbar_init(sb + B_AFULL + i * 8, 1);
    for (int i = 0; i < 6; i++) { mbar_init(sb + B_AFREE + i * 8, 4); mbar_init(sb + B_OWN + i * 8, 4); }
    for (int i = 0; i < 2; i++) { mbar_init(sb + B_STAT + i * 8, 1); mbar_init(sb + B_PRDY + i * 8, 1); mbar_init(sb + B_PFREE + i * 8, 4); }
    mbar_init(sb + B_CSRDY, 1); mbar_init(sb + B_CSRDY + 8, 1); mbar_init(sb + B_KVDONE, 8); mbar_init(sb + B_KVRDY, 1);
    asm volatile("fence.mbarrier_init.release.cluster;" ::: "memory");
  }
  const uint32_t epoch = ld_relaxed(g_epoch + bid * 8);
  __syncthreads();
  asm volatile("barrier.cluster.arrive.relaxed.aligned;" ::: "memory");

  if (warp >= 8) {
  asm volatile("setmaxnreg.dec.sync.aligned.u32 72;");
  if (warp == 8) {
    uint32_t st = 0;
    auto acquire = [&](uint32_t bytes) -> uint32_t {
      const uint32_t s = st & 3;
      mbar_wait(sb + B_BEMPTY + s * 8, ((st >> 2) & 1) ^ 1);
      st++;
      return s;
    };
    if (lane == 0) { prefetch_map(&tm_wqkv); prefetch_map(&tm_wo); prefetch_map(&tm_w1); prefetch_map(&tm_w2); }
#pragma unroll 1
    for (int l = 0; l < 2; l++) {
#pragma unroll 1
      for (int i = 0; i < 8; i++) {
        const uint32_t s = acquire(0), dst = sb + SM_RING + s * SLOT, fb = sb + B_BFULL + s * 8;
        const int kc = (r + i) & 7;
        if (elect_one()) { mbar_expect_tx(fb, 16384); tma_load(dst, &tm_wqkv, 512 + 64 * r, 64 * kc, fb); tma_load(dst + 8192, &tm_wqkv, 1024 + 64 * r, 64 * kc, fb); }
      }
#pragma unroll 1
      for (int i = 0; i < 4; i++) {
        const uint32_t s = acquire(0), dst = sb + SM_RING + s * SLOT, fb = sb + B_BFULL + s * 8;
        if (elect_one()) { mbar_expect_tx(fb, 16384); tma_load(dst, &tm_wqkv, 64 * r, 64 * ((r + 2 * i) & 7), fb); tma_load(dst + 8192, &tm_wqkv, 64 * r, 64 * ((r + 2 * i + 1) & 7), fb); }
      }
#pragma unroll 1
      for (int i = 0; i < 4; i++) {
        const uint32_t s = acquire(0), dst = sb + SM_RING + s * SLOT, fb = sb + B_BFULL + s * 8;
        if (elect_one()) { mbar_expect_tx(fb, 16384); tma_load(dst, &tm_wo, 64 * r, 64 * ((r + 2 * i) & 7), fb); tma_load(dst + 8192, &tm_wo, 64 * r, 64 * ((r + 2 * i + 1) & 7), fb); }
      }
#pragma unroll 1
      for (int i = 0; i < 8; i++) {
        const uint32_t s = acquire(0), dst = sb + SM_RING + s * SLOT, fb = sb + B_BFULL + s * 8;
        const int kc = (r + i) & 7;
        if (elect_one()) { mbar_expect_tx(fb, 24576); tma_load(dst, &tm_w1, kHS * r, 64 * kc, fb); tma_load(dst + 8192, &tm_w1, kHS * r + 64, 64 * kc, fb); tma_load(dst + 16384, &tm_w1, kHS * r + 128, 64 * kc, fb); }
      }
#pragma unroll 1
      for (int i = 0; i < 8; i++) {
        const uint32_t s = acquire(0), dst = sb + SM_RING + s * SLOT, fb = sb + B_BFULL + s * 8;
        const int j = (r + (i & ~1)) & 7;
        if (elect_one()) { mbar_expect_tx(fb, kHS * 128); tma_load(dst, &tm_w2, 64 * ((i & 1) ? r : (r ^ 1)), kHS * j, fb); }
      }
    }
    asm volatile("barrier.cluster.wait.aligned;" ::: "memory");
  } else if (warp == 9 || warp == 10) {
    const int h = warp - 9, half = cb * 2 + h;
    const uint32_t abase = sb + h * 65536, afull = sb + B_AFULL + h * 64, afree = sb + B_AFREE + h * 24, own = sb + B_OWN + h * 24;
    uint32_t* flags = g_flags + half * 32;
    if (elect_one()) {
      prefetch_map(&tm_x);
      for (int i = 0; i < 8; i++) { mbar_expect_tx(afull + i * 8, 8192); tma_load(abase + i * 8192, &tm_x, 64 * ((r + i) & 7), 128 * cb + 64 * h, afull + i * 8); }
    }
    __syncwarp();
    const uint32_t ev0 = epoch * 16, tag = (epoch + 1) & 1;
    colsum_task(wqkv + (1 + h) * 512 + 64 * r + 8 * (lane & 7), 3 * kD, true, 32 * cb, g_cs + ((r * 2 + 0) * 16 + cb) * 48 + (1 + h) * 16 + 2 * (lane & 7), lane, tag);
    gather_stats(g_stats + (0 * 32 + half) * 512, sb + SM_STAT + h * 512, sb + B_STAT + h * 8, lane, tag);
    asm volatile("barrier.cluster.wait.aligned;" ::: "memory");
    uint32_t p0 = 0;
#pragma unroll 1
    for (int l = 0; l < 2; l++) {
      const uint32_t ev = ev0 + l * 6;
      mbar_wait(own, p0);
      STAMP(2 + h, l * 16 + 0);
      publish_chunk(g_act + (0 * 32 + half) * 4096 + r * 512, abase, flags + r, ev + 1, lane);
      STAMP(2 + h, l * 16 + 11);
      mbar_wait(afree, p0); p0 ^= 1;
      fetch_chunks(g_act + (0 * 32 + half) * 4096, flags, abase, afull, r, ev + 1, lane);
      STAMP(2 + h, l * 16 + 1);
      mbar_wait(own, p0);
      STAMP(2 + h, l * 16 + 2);
      publish_chunk(g_act + (1 * 32 + half) * 4096 + r * 512, abase, flags + r, ev + 2, lane);
      mbar_wait(afree, p0); p0 ^= 1;
      STAMP(2 + h, l * 16 + 12);
      gather_stats(g_stats + ((2 * l + 1) * 32 + half) * 512, sb + SM_STAT + h * 512, sb + B_STAT + h * 8, lane, tag);
      STAMP(2 + h, l * 16 + 3);
      fetch_chunks(g_act + (1 * 32 + half) * 4096, flags, abase, afull, r, ev + 2, lane);
      STAMP(2 + h, l * 16 + 4);
      uint4* hb = g_h + half * 8 * 1536;
      mbar_wait(afree, p0);
      mbar_wait(own, p0); p0 ^= 1;
      STAMP(2 + h, l * 16 + 5);
      if (lane == 0) { bulk_s2g(hb + r * 1536, abase, 8192); bulk_commit(); }
      mbar_wait(own + 8, l);
      if (lane == 0) { bulk_s2g(hb + r * 1536 + 512, abase + 8192, 8192); bulk_commit(); }
      mbar_wait(own + 16, l);
      if (lane == 0) {
        bulk_s2g(hb + r * 1536 + 1024, abase + 16384, 6144); bulk_commit();
        bulk_wait<0>(); st_relaxed_u32(flags + r, ev + 3);
      }
      __syncwarp();
      STAMP(2 + h, l * 16 + 6);
      wait_flags(flags + ((r + 2 * (lane & 3)) & 7), ev + 3);
      STAMP(2 + h, l * 16 + 13);
#pragma unroll 1
      for (int b = 3; b < 12; b++) {
        const int t = b / 3, bb = b - 3 * t, j = (r + 2 * t) & 7, slot = b & 7;
        if (b == 8) mbar_wait(afree + 8, l);
        if (b == 11) mbar_wait(afree + 16, l);
        if (elect_one()) {
          const uint32_t bytes = bb == 2 ? 6144 : 8192;
          mbar_expect_tx(afull + slot * 8, bytes);
          bulk_g2s(abase + slot * 8192, hb + j * 1536 + bb * 512, bytes, afull + slot * 8);
        }
        __syncwarp();
      }
      STAMP(2 + h, l * 16 + 7);
      mbar_wait(own, p0);
      STAMP(2 + h, l * 16 + 8);
      if (l == 0) {
        publish_chunk(g_act + (2 * 32 + half) * 4096 + r * 512, abase, flags + r, ev + 6, lane);
        mbar_wait(afree, p0); p0 ^= 1;
        gather_stats(g_stats + (2 * 32 + half) * 512, sb + SM_STAT + h * 512, sb + B_STAT + h * 8, lane, tag);
        STAMP(2 + h, l * 16 + 9);
        fetch_chunks(g_act + (2 * 32 + half) * 4096, flags, abase, afull, r, ev + 6, lane);
      } else if (lane == 0) {
        tma_store(&tm_out, abase, 64 * r, 128 * cb + 64 * h); bulk_commit(); bulk_wait<0>();
      }
      STAMP(2 + h, l * 16 + 10);
    }
  } else {
    const uint32_t par = epoch & 1, tag = par ^ 1;
    colsum_task(wqkv + 64 * r + 8 * (lane & 7), 3 * kD, true, 32 * cb, g_cs + ((r * 2 + 0) * 16 + cb) * 48 + 2 * (lane & 7), lane, tag);
    for (int i = lane; i < 136; i += 32) g_kv[(((par ^ 1) * 2 + (i >= 68)) * 8 + r) * 1088 + cb * 68 + (i >= 68 ? i - 68 : i)] = 0.f;
    colsum_gather(g_cs + (r * 2 + 0) * 16 * 48, sb + SM_CS, 48, sb + B_CSRDY, lane, tag);
    STAMP(2, 48);
    if (lane == 1) prefetch_l2((const char*)wo + bid * 4096, 4096);
    if (lane == 2) prefetch_l2((const char*)w2 + bid * 11008, 11008);
#pragma unroll 1
    for (int b = 0; b < 3; b++) {
      const int col = 64 * b + 8 * (lane & 7);
      colsum_task(w1 + kHS * r + col, kFF, col < kHS && kHS * r + col < kFF, 32 * cb, g_cs + ((r * 2 + 1) * 16 + cb) * 48 + b * 16 + 2 * (lane & 7), lane, tag);
    }
    STAMP(2, 49);
    asm volatile("barrier.cluster.wait.aligned;" ::: "memory");
    const uint32_t target = (epoch + 1) * 16;
    const int g = lane >> 2, t = lane & 3;
#pragma unroll 1
    for (int l = 0; l < 2; l++) {
      mbar_wait(sb + B_KVDONE, l);
      STAMP(2, 50 + l * 4);
      if (lane == 0) { fence_gpu(); red_add_u32(g_cnt + (l * 8 + r) * 32, 1); }
      STAMP(2, 51 + l * 4);
      wait_flag_acq(g_cnt + (l * 8 + r) * 32, target);
      STAMP(2, 52 + l * 4);
      const float* kv = g_kv + ((par * 2 + l) * 8 + r) * 1088;
      float2 v[24];
#pragma unroll
      for (int hh = 0; hh < 4; hh++) {
        v[hh * 6 + 0] = ld_relaxed_f2(kv + hh * 272 + g * 16 + 2 * t);        v[hh * 6 + 1] = ld_relaxed_f2(kv + hh * 272 + g * 16 + 8 + 2 * t);
        v[hh * 6 + 2] = ld_relaxed_f2(kv + hh * 272 + (8 + g) * 16 + 2 * t);  v[hh * 6 + 3] = ld_relaxed_f2(kv + hh * 272 + (8 + g) * 16 + 8 + 2 * t);
        v[hh * 6 + 4] = ld_relaxed_f2(kv + hh * 272 + 256 + 2 * t);           v[hh * 6 + 5] = ld_relaxed_f2(kv + hh * 272 + 256 + 8 + 2 * t);
      }
#pragma unroll
      for (int i = 0; i < 12; i++) sts_u2(sb + SM_RING + 16384 + i * 256 + lane * 8, pack_bf16(v[2 * i].x, v[2 * i].y), pack_bf16(v[2 * i + 1].x, v[2 * i + 1].y));
      __syncwarp();
      if (lane == 0) mbar_arrive(sb + B_KVRDY);
      STAMP(2, 53 + l * 4);
      if (l == 0) colsum_gather(g_cs + (r * 2 + 1) * 16 * 48, sb + SM_CS + 768, 44, sb + B_CSRDY + 8, lane, tag);
    }
    if (lane == 0) g_epoch[bid * 8] = epoch + 1;
  }
  } else {
    asm volatile("setmaxnreg.inc.sync.aligned.u32 216;");
    const int wg = warp >> 2, wq = warp & 3, g = lane >> 2, t = lane & 3, half = cb * 2 + wg;
    const uint32_t abase = sb + wg * 65536, afull = sb + B_AFULL + wg * 64, afree = sb + B_AFREE + wg * 24, own = sb + B_OWN + wg * 24;
    const uint32_t ring = sb + SM_RING;
    const int mrow = 16 * wq + 8 * ((lane >> 3) & 1) + (lane & 7);
    const uint32_t sw_row = mrow * 128, sw_x = lane & 7, sw_hi = lane >> 4;
    auto sw_addr = [&](uint32_t base, int s) -> uint32_t { return base + sw_row + (((2 * s + sw_hi) ^ sw_x) << 4); };
    STAMP(wg, 62);
    const uint32_t tag = (epoch + 1) & 1;
    uint32_t xr[16];
    uint32_t aph = 0;
    uint32_t st = 0;
    uint32_t sph = 0;
    auto wait_a = [&](int i) { mbar_wait(afull + i * 8, (aph >> i) & 1); aph ^= 1u << i; };
    auto wait_b = [&]() -> uint32_t { const uint32_t s = st & 3; mbar_wait(sb + B_BFULL + s * 8, (st >> 2) & 1); st++; return ring + s * SLOT; };
    auto release_b = [&](uint32_t idx) { if (lane == 0) mbar_arrive(sb + B_BEMPTY + (idx & 3) * 8); };
    auto signal = [&](uint32_t bar) { __syncwarp(); if (lane == 0) mbar_arrive(bar); };
    const uint32_t chk_off = (16 * wq + g) * 128 + (((2 * t) ^ g) << 4);
    auto fetch_ok = [&](int i, const uint4* gbuf, uint32_t tg) {
      wait_a(i);
      const uint32_t base = abase + i * 8192;
      uint32_t cnt = 0;
      while (!__all_sync(0xffffffff, (((lds_u32(base + chk_off) ^ tg) | (lds_u32(base + chk_off + 1024) ^ tg)) & 1u) == 0)) {
        const uint4* src = gbuf + ((r + i) & 7) * 512 + wq * 128 + lane;
#pragma unroll
        for (int u = 0; u < 4; u++) sts_u4(base + wq * 2048 + u * 512 + lane * 16, ld_relaxed_u4(src + u * 32));
        fence_async_smem();
        __syncwarp();
        if (++cnt > SPIN_LIMIT) __trap();
      }
    };
    const uint32_t hchk_off = (lane >> 4) * 2048 + ((lane >> 3) & 1) * 1024 + (2 * wq + ((lane >> 2) & 1)) * 128 + (lane & 3) * 32 + g * 4;
    auto fetch_h_ok = [&](int slot, const uint4* gsrc, bool three, uint32_t tg) {
      wait_a(slot);
      const uint32_t base = abase + slot * 8192;
      uint32_t cnt = 0;
      while (!__all_sync(0xffffffff, (((lds_u32(base + hchk_off) ^ tg) | (lds_u32(base + hchk_off + ((three && lane >= 16) ? 0 : 4096)) ^ tg)) >> 31) == 0)) {
        const uint32_t off = (lane >> 4) * 1024 + wq * 256 + (lane & 15) * 16;
        for (int u = 0; u < (three ? 3 : 4); u++) sts_u4(base + u * 2048 + off, ld_relaxed_u4(gsrc + (u * 2048 + off) / 16));
        fence_async_smem();
        __syncwarp();
        if (++cnt > SPIN_LIMIT) __trap();
      }
    };
    const uint32_t tmask = t == 0 ? 1u : 0u;
    auto store_chunk = [&](const uint32_t (&v)[16], uint32_t tg  , uint32_t msk) {
#pragma unroll
      for (int s = 0; s < 4; s++) stsm4(sw_addr(abase, s), (v[4 * s] & ~msk) | tg, (v[4 * s + 1] & ~msk) | tg, v[4 * s + 2], v[4 * s + 3]);
      fence_async_smem();
      signal(own);
    };
    float2* stat_dst = g_stats + half * 512 + (16 * wq + g) * 8 + r;
    const uint32_t stat_sm = sb + SM_STAT + (wg * 64 + 16 * wq + g) * 8;
    const uint32_t cs_sm = sb + SM_CS + 8 * t;

    wait_a(0);
#pragma unroll
    for (int s = 0; s < 4; s++) ldsm4(sw_addr(abase, s), xr[4 * s], xr[4 * s + 1], xr[4 * s + 2], xr[4 * s + 3]);
    asm volatile("barrier.cluster.wait.aligned;" ::: "memory");
    STAMP(wg, 63);

#pragma unroll 1
    for (int l = 0; l < 2; l++) {
      const uint32_t ltag = l ^ 1;
      float rs0, rs1;
      {
        float ak[32], av[32], aq[32];
        STAMP(wg, l * 24 + 0);
        {
          const uint32_t bs = wait_b();
          const uint64_t da = descA(abase), db = descB(bs, 8192);
          wg_fence();
          wgmma_n128_init(ak, av, da, db);
#pragma unroll
          for (int k = 1; k < 4; k++) wgmma_n128(ak, av, da + 2 * k, db + 128 * k, 1);
          wg_commit();
          if (l == 0) publish_stats(xr, stat_dst, t, tag);
        }
#pragma unroll 1
        for (int i = 1; i < 8; i++) {
          if (l == 0) wait_a(i); else fetch_ok(i, g_act + (2 * 32 + half) * 4096, tag);
          if (i == 1) STAMP(wg, l * 24 + 19);
          const uint32_t bs = wait_b();
          const uint64_t da = descA(abase + i * 8192), db = descB(bs, 8192);
          wg_fence();
#pragma unroll
          for (int k = 0; k < 4; k++) wgmma_n128(ak, av, da + 2 * k, db + 128 * k, 1);
          wg_commit();
          wg_wait<1>(); release_b(st - 2);
        }
        STAMP(wg, l * 24 + 1);
#pragma unroll
        for (int i = 0; i < 3; i++) {
          const uint32_t bs = wait_b();
          const uint64_t da = descA(abase + i * 16384), db = descB(bs, 8192);
          wg_fence();
#pragma unroll
          for (int k = 0; k < 8; k++) {
            if (i == 0 && k == 0) wgmma_n64_init(aq, da, db); else wgmma_n64(aq, da + (k >> 2) * 512 + 2 * (k & 3), db + 128 * k, 1);
          }
          wg_commit();
          if (i == 0) { wg_wait<1>(); release_b(st - 2); }
        }
        fence_regs(ak); fence_regs(av);
        if (l == 0) mbar_wait(sb + B_CSRDY, 0);
        mbar_wait(sb + B_STAT + wg * 8, sph); sph ^= 1;
        const float2 s0 = lds_f2(stat_sm), s1 = lds_f2(stat_sm + 64);
        const float y0 = s0.x * 1.4426950408889634f, y1 = s1.x * 1.4426950408889634f;
        STAMP(wg, l * 24 + 2);
        const uint32_t pk_s = ring + (2 * wg) * SLOT + 16384, v_s = ring + (2 * wg + 1) * SLOT + 16384;
        {
          float2 c[16];
#pragma unroll
          for (int j = 0; j < 16; j++) c[j] = lds_f2(cs_sm + (64 + 8 * j) * 4);
          uint32_t pk[16], pv[16];
#pragma unroll
          for (int j = 0; j < 8; j++) {
            pk[2 * j] = pack_bf16(phi_y(y0 * fmaf(s0.y, c[j].x, ak[4 * j])), phi_y(y0 * fmaf(s0.y, c[j].y, ak[4 * j + 1])));
            pk[2 * j + 1] = pack_bf16(phi_y(y1 * fmaf(s1.y, c[j].x, ak[4 * j + 2])), phi_y(y1 * fmaf(s1.y, c[j].y, ak[4 * j + 3])));
            pv[2 * j] = pack_bf16(s0.x * fmaf(s0.y, c[8 + j].x, av[4 * j]), s0.x * fmaf(s0.y, c[8 + j].y, av[4 * j + 1]));
            pv[2 * j + 1] = pack_bf16(s1.x * fmaf(s1.y, c[8 + j].x, av[4 * j + 2]), s1.x * fmaf(s1.y, c[8 + j].y, av[4 * j + 3]));
          }
#pragma unroll
          for (int s = 0; s < 4; s++) {
            stsm4(sw_addr(pk_s, s), pk[4 * s], pk[4 * s + 1], pk[4 * s + 2], pk[4 * s + 3]);
            stsm4(sw_addr(v_s, s), pv[4 * s], pv[4 * s + 1], pv[4 * s + 2], pv[4 * s + 3]);
          }
        }
        wg_bar(wg);
        {
          float c0[4] = {0.f, 0.f, 0.f, 0.f}, c1[4] = {0.f, 0.f, 0.f, 0.f}, z0[4] = {0.f, 0.f, 0.f, 0.f}, z1[4] = {0.f, 0.f, 0.f, 0.f};
          const int m = lane >> 3;
#pragma unroll
          for (int ks = 0; ks < 4; ks++) {
            uint32_t a0, a1, a2, a3, b0, b1, b2, b3;
            const int ra = 16 * ks + 8 * (m >> 1) + (lane & 7), rb = 16 * ks + 8 * (m & 1) + (lane & 7);
            ldsm4t(v_s + ra * 128 + (((2 * wq + (m & 1)) ^ (lane & 7)) << 4), a0, a1, a2, a3);
            ldsm4t(pk_s + rb * 128 + (((2 * wq + (m >> 1)) ^ (lane & 7)) << 4), b0, b1, b2, b3);
            mma16816(c0, a0, a1, a2, a3, b0, b1);
            mma16816(c1, a0, a1, a2, a3, b2, b3);
            mma16816(z0, 0x3f803f80u, 0x3f803f80u, 0x3f803f80u, 0x3f803f80u, b0, b1);
            mma16816(z1, 0x3f803f80u, 0x3f803f80u, 0x3f803f80u, 0x3f803f80u, b2, b3);
          }
          float* kv = g_kv + (((epoch & 1) * 2 + l) * 8 + r) * 1088 + wq * 272;
          red_add_f2(kv + g * 16 + 2 * t, c0[0], c0[1]); red_add_f2(kv + (g + 8) * 16 + 2 * t, c0[2], c0[3]);
          red_add_f2(kv + g * 16 + 8 + 2 * t, c1[0], c1[1]); red_add_f2(kv + (g + 8) * 16 + 8 + 2 * t, c1[2], c1[3]);
          if (g == 0) { red_add_f2(kv + 256 + 2 * t, z0[0], z0[1]); red_add_f2(kv + 256 + 8 + 2 * t, z1[0], z1[1]); }
          signal(sb + B_KVDONE);
        }
        STAMP(wg, l * 24 + 3);
        wg_wait<2>(); release_b(st - 3);
        {
          const uint32_t bs = wait_b();
          const uint64_t da = descA(abase + 3 * 16384), db = descB(bs, 8192);
          wg_fence();
#pragma unroll
          for (int k = 0; k < 8; k++) wgmma_n64(aq, da + (k >> 2) * 512 + 2 * (k & 3), db + 128 * k, 1);
          wg_commit();
        }
        float2 c[8];
#pragma unroll
        for (int j = 0; j < 8; j++) c[j] = lds_f2(cs_sm + 8 * j * 4);
        wg_wait<2>(); release_b(st - 3);
        wg_wait<1>(); release_b(st - 2);
        wg_wait<0>(); release_b(st - 1);
        fence_regs(aq);
        if (lane == 0) mbar_arrive(afree);
        STAMP(wg, l * 24 + 4);
        uint32_t pq[16];
#pragma unroll
        for (int j = 0; j < 8; j++) {
          pq[2 * j] = pack_bf16(phi_y(y0 * fmaf(s0.y, c[j].x, aq[4 * j])), phi_y(y0 * fmaf(s0.y, c[j].y, aq[4 * j + 1])));
          pq[2 * j + 1] = pack_bf16(phi_y(y1 * fmaf(s1.y, c[j].x, aq[4 * j + 2])), phi_y(y1 * fmaf(s1.y, c[j].y, aq[4 * j + 3])));
        }
        STAMP(wg, l * 24 + 5);
        mbar_wait(sb + B_KVRDY, l);
        STAMP(wg, l * 24 + 6);
        uint2 f[12];
#pragma unroll
        for (int i = 0; i < 12; i++) f[i] = lds_u2(ring + 16384 + i * 256 + lane * 8);
        float cn[4][8], cz[4][4];
#pragma unroll
        for (int hh = 0; hh < 4; hh++) {
          float c0[4] = {0.f, 0.f, 0.f, 0.f}, c1[4] = {0.f, 0.f, 0.f, 0.f};
          cz[hh][0] = cz[hh][1] = cz[hh][2] = cz[hh][3] = 0.f;
          mma16816(cz[hh], pq[4 * hh], pq[4 * hh + 1], pq[4 * hh + 2], pq[4 * hh + 3], f[3 * hh + 2].x, f[3 * hh + 2].y);
          mma16816(c0, pq[4 * hh], pq[4 * hh + 1], pq[4 * hh + 2], pq[4 * hh + 3], f[3 * hh].x, f[3 * hh].y);
          mma16816(c1, pq[4 * hh], pq[4 * hh + 1], pq[4 * hh + 2], pq[4 * hh + 3], f[3 * hh + 1].x, f[3 * hh + 1].y);
#pragma unroll
          for (int u = 0; u < 4; u++) { cn[hh][u] = c0[u]; cn[hh][4 + u] = c1[u]; }
        }
        uint32_t o[16];
#pragma unroll
        for (int hh = 0; hh < 4; hh++) {
          const float i0 = rcp(cz[hh][0] + 1e-6f), i1 = rcp(cz[hh][2] + 1e-6f);
          o[4 * hh] = pack_bf16(cn[hh][0] * i0, cn[hh][1] * i0); o[4 * hh + 1] = pack_bf16(cn[hh][2] * i1, cn[hh][3] * i1);
          o[4 * hh + 2] = pack_bf16(cn[hh][4] * i0, cn[hh][5] * i0); o[4 * hh + 3] = pack_bf16(cn[hh][6] * i1, cn[hh][7] * i1);
        }
        store_chunk(o, ltag & tmask, tmask);
        wg_bar(wg);
        STAMP(wg, l * 24 + 7);
      }
      {
        float acc[32];
        const uint4* gbuf = g_act + (0 * 32 + half) * 4096;
        uint32_t bs = wait_b();
        {
          const uint64_t da = descA(abase), db = descB(bs, 8192);
          wg_fence();
          wgmma_n64_init(acc, da, db);
#pragma unroll
          for (int k = 1; k < 4; k++) wgmma_n64(acc, da + 2 * k, db + 128 * k, 1);
          wg_commit();
        }
#pragma unroll 1
        for (int i = 1; i < 8; i++) {
          if ((i & 1) == 0) bs = wait_b();
          fetch_ok(i, gbuf, ltag);
          if (i == 1) STAMP(wg, l * 24 + 8);
          const uint64_t da = descA(abase + i * 8192), db = descB(bs + (i & 1) * 8192, 8192);
          wg_fence();
#pragma unroll
          for (int k = 0; k < 4; k++) wgmma_n64(acc, da + 2 * k, db + 128 * k, 1);
          wg_commit();
          if ((i & 1) == 0) { wg_wait<1>(); release_b(st - 2); }
        }
        wg_wait<0>(); release_b(st - 1);
        fence_regs(acc);
        if (lane == 0) mbar_arrive(afree);
        STAMP(wg, l * 24 + 9);
#pragma unroll
        for (int j = 0; j < 8; j++) {
          xr[2 * j] = pack_bf16(bf_lo(xr[2 * j]) + acc[4 * j], bf_hi(xr[2 * j]) + acc[4 * j + 1]);
          xr[2 * j + 1] = pack_bf16(bf_lo(xr[2 * j + 1]) + acc[4 * j + 2], bf_hi(xr[2 * j + 1]) + acc[4 * j + 3]);
        }
        store_chunk(xr, ltag & tmask, tmask);
        publish_stats(xr, stat_dst + (2 * l + 1) * 32 * 512, t, tag);
        wg_bar(wg);
        STAMP(wg, l * 24 + 10);
      }
      {
        float acc[88];
        const uint4* gbuf = g_act + (1 * 32 + half) * 4096;
        {
          const uint32_t bs = wait_b();
          const uint64_t da = descA(abase), db = descB(bs, 8192);
          wg_fence();
          wgmma_n176_init(acc, da, db);
#pragma unroll
          for (int k = 1; k < 4; k++) wgmma_n176(acc, da + 2 * k, db + 128 * k, 1);
          wg_commit();
        }
#pragma unroll 1
        for (int i = 1; i < 8; i++) {
          fetch_ok(i, gbuf, ltag);
          if (i == 1) STAMP(wg, l * 24 + 11);
          const uint32_t bs = wait_b();
          const uint64_t da = descA(abase + i * 8192), db = descB(bs, 8192);
          wg_fence();
#pragma unroll
          for (int k = 0; k < 4; k++) wgmma_n176(acc, da + 2 * k, db + 128 * k, 1);
          wg_commit();
          wg_wait<1>(); release_b(st - 2);
        }
        if (l == 0) mbar_wait(sb + B_CSRDY + 8, 0);
        mbar_wait(sb + B_STAT + wg * 8, sph); sph ^= 1;
        const float2 s0 = lds_f2(stat_sm), s1 = lds_f2(stat_sm + 64);
        float2 c[22];
#pragma unroll
        for (int j = 0; j < 22; j++) c[j] = lds_f2(cs_sm + (192 + 8 * j) * 4);
        const uint32_t sgn = ltag ? 0x80008000u : 0u;
        rs0 = ltag ? -s0.x : s0.x; rs1 = ltag ? -s1.x : s1.x;
        wg_wait<0>(); release_b(st - 1);
        fence_regs(acc);
        if (lane == 0) mbar_arrive(afree);
        STAMP(wg, l * 24 + 12);
        const uint32_t hrow = abase + (lane >> 4) * 1024 + (2 * wq + ((lane >> 3) & 1)) * 128 + (lane & 7) * 16;
#pragma unroll
        for (int b = 0; b < 3; b++) {
          uint32_t p[16];
#pragma unroll
          for (int u = 0; u < (b == 2 ? 6 : 8); u++) {
            const int j = 8 * b + u;
            p[2 * u] = pack_bf16_relu(fmaf(s0.y, c[j].x, acc[4 * j]), fmaf(s0.y, c[j].y, acc[4 * j + 1])) ^ sgn;
            p[2 * u + 1] = pack_bf16_relu(fmaf(s1.y, c[j].x, acc[4 * j + 2]), fmaf(s1.y, c[j].y, acc[4 * j + 3])) ^ sgn;
          }
#pragma unroll
          for (int s = 0; s < (b == 2 ? 3 : 4); s++) stsm4(hrow + (4 * b + s) * 2048, p[4 * s], p[4 * s + 1], p[4 * s + 2], p[4 * s + 3]);
          fence_async_smem(); signal(own + b * 8);
        }
        wg_bar(wg);
        STAMP(wg, l * 24 + 13);
      }
      {
        float ap[32], ao[32];
        float bp[32], bo[32];
        const uint4* hb = g_h + half * 8 * 1536;
        const uint32_t htag = ltag << 31;
        {
          const uint32_t bs = wait_b(); wait_b();
          const uint64_t db = descB(bs, SLOT), da = descH(abase);
          wg_fence();
          wgmma_n128_init(ap, ao, da, db);
#pragma unroll
          for (int k = 1; k < 11; k++) wgmma_n128(ap, ao, da + 128 * k, db + 128 * k, 1);
          wg_commit();
        }
#pragma unroll 1
        for (int tt = 1; tt < 3; tt++) {
          const uint32_t bs = wait_b(); wait_b();
          const uint64_t db = descB(bs, SLOT);
#pragma unroll
          for (int bb = 0; bb < 3; bb++) {
            const int slot = (3 * tt + bb) & 7;
            fetch_h_ok(slot, hb + ((r + 2 * tt) & 7) * 1536 + bb * 512, bb == 2, htag);
            if (tt == 1 && bb == 0) STAMP(wg, l * 24 + 14);
            const uint64_t da = descH(abase + slot * 8192);
            wg_fence();
#pragma unroll
            for (int k = 0; k < (bb == 2 ? 3 : 4); k++) wgmma_n128(ap, ao, da + 128 * k, db + 128 * (4 * bb + k), 1);
            wg_commit();
            if (bb == 0) {
              wg_wait<1>(); release_b(st - 4); release_b(st - 3);
              if (lane == 0) mbar_arrive(afree + 8 * tt);
              if (tt == 2 && lane == 0) { mbar_arrive_remote(mapa(sb + B_PFREE + wg * 8, (r & 1) ^ 1)); if (wq == 0) mbar_expect_tx(sb + B_PRDY + wg * 8, 8192); }
            }
          }
        }
        {
          const uint32_t bs0 = wait_b();
          const uint64_t db = descB(bs0, SLOT);
#pragma unroll
          for (int bb = 0; bb < 3; bb++) {
            fetch_h_ok(1 + bb, hb + ((r + 6) & 7) * 1536 + bb * 512, bb == 2, htag);
            const uint64_t da = descH(abase + (1 + bb) * 8192);
            wg_fence();
#pragma unroll
            for (int k = 0; k < (bb == 2 ? 3 : 4); k++) {
              if (bb == 0 && k == 0) wgmma_n64_init(bp, da, db); else wgmma_n64(bp, da + 128 * k, db + 128 * (4 * bb + k), 1);
            }
            wg_commit();
            if (bb == 0) { wg_wait<1>(); release_b(st - 3); release_b(st - 2); }
          }
          const uint32_t bs1 = wait_b();
          const uint64_t db1 = descB(bs1, SLOT), da = descH(abase + 8192);
          wg_fence();
          wgmma_n64_init(bo, da, db1);
#pragma unroll
          for (int k = 1; k < 11; k++) wgmma_n64(bo, da + 128 * k, db1 + 128 * k, 1);
          wg_commit();
          wg_wait<1>(); release_b(st - 2);
          fence_regs(ap); fence_regs(ao); fence_regs(bp);
          STAMP(wg, l * 24 + 15);
          mbar_wait(sb + B_PFREE + wg * 8, l);
          const uint32_t rdst = mapa(abase + 4 * 8192 + (tid & 127) * 16, (r & 1) ^ 1), rbar = mapa(sb + B_PRDY + wg * 8, (r & 1) ^ 1);
#pragma unroll
          for (int i = 0; i < 4; i++)
            st_async_v4(rdst + i * 2048, pack_bf16(ap[8 * i] + bp[8 * i], ap[8 * i + 1] + bp[8 * i + 1]), pack_bf16(ap[8 * i + 2] + bp[8 * i + 2], ap[8 * i + 3] + bp[8 * i + 3]),
                        pack_bf16(ap[8 * i + 4] + bp[8 * i + 4], ap[8 * i + 5] + bp[8 * i + 5]), pack_bf16(ap[8 * i + 6] + bp[8 * i + 6], ap[8 * i + 7] + bp[8 * i + 7]), rbar);
          wg_wait<0>(); release_b(st - 1);
          fence_regs(bo);
#pragma unroll
          for (int i = 0; i < 32; i++) ao[i] += bo[i];
          STAMP(wg, l * 24 + 16);
          mbar_wait(sb + B_PRDY + wg * 8, l);
          STAMP(wg, l * 24 + 17);
          uint4 p[4];
#pragma unroll
          for (int i = 0; i < 4; i++) p[i] = lds_u4(abase + 4 * 8192 + i * 2048 + (tid & 127) * 16);
#pragma unroll
          for (int i = 0; i < 4; i++) {
            xr[4 * i] = pack_bf16(fmaf(rs0, ao[8 * i] + bf_lo(p[i].x), bf_lo(xr[4 * i])), fmaf(rs0, ao[8 * i + 1] + bf_hi(p[i].x), bf_hi(xr[4 * i])));
            xr[4 * i + 1] = pack_bf16(fmaf(rs1, ao[8 * i + 2] + bf_lo(p[i].y), bf_lo(xr[4 * i + 1])), fmaf(rs1, ao[8 * i + 3] + bf_hi(p[i].y), bf_hi(xr[4 * i + 1])));
            xr[4 * i + 2] = pack_bf16(fmaf(rs0, ao[8 * i + 4] + bf_lo(p[i].z), bf_lo(xr[4 * i + 2])), fmaf(rs0, ao[8 * i + 5] + bf_hi(p[i].z), bf_hi(xr[4 * i + 2])));
            xr[4 * i + 3] = pack_bf16(fmaf(rs1, ao[8 * i + 6] + bf_lo(p[i].w), bf_lo(xr[4 * i + 3])), fmaf(rs1, ao[8 * i + 7] + bf_hi(p[i].w), bf_hi(xr[4 * i + 3])));
          }
          signal(afree);
          store_chunk(xr, l == 0 ? (tag & tmask) : 0u, l == 0 ? tmask : 0u);
          if (l == 0) publish_stats(xr, stat_dst + 2 * 32 * 512, t, tag);
          wg_bar(wg);
          STAMP(wg, l * 24 + 18);
        }
      }
      if (l == 0) asm volatile("" ::: "memory");
    }

  }
}

typedef CUresult (*EncodeFn)(CUtensorMap*, CUtensorMapDataType, cuuint32_t, void*, const cuuint64_t*, const cuuint64_t*, const cuuint32_t*,
                             const cuuint32_t*, CUtensorMapInterleave, CUtensorMapSwizzle, CUtensorMapL2promotion, CUtensorMapFloatOOBfill);

CUtensorMap make_map(EncodeFn enc, const void* ptr, uint64_t cols, uint64_t rows, uint32_t box_rows) {
  CUtensorMap m;
  cuuint64_t gd[2] = {cols, rows}, gs[1] = {cols * 2};
  cuuint32_t bd[2] = {64, box_rows}, es[2] = {1, 1};
  enc(&m, CU_TENSOR_MAP_DATA_TYPE_BFLOAT16, 2, const_cast<void*>(ptr), gd, gs, bd, es, CU_TENSOR_MAP_INTERLEAVE_NONE,
      CU_TENSOR_MAP_SWIZZLE_128B, CU_TENSOR_MAP_L2_PROMOTION_L2_128B, CU_TENSOR_MAP_FLOAT_OOB_FILL_NONE);
  return m;
}

}

extern "C" void kernel_launch(void* const* d_in, const int* in_sizes, int n_in, void* d_out, int out_size) {
  (void)in_sizes; (void)n_in; (void)out_size;
  const __nv_bfloat16* x = (const __nv_bfloat16*)d_in[0];
  const __nv_bfloat16* wqkv = (const __nv_bfloat16*)d_in[1];
  const __nv_bfloat16* wo = (const __nv_bfloat16*)d_in[2];
  const __nv_bfloat16* w1 = (const __nv_bfloat16*)d_in[4];
  const __nv_bfloat16* w2 = (const __nv_bfloat16*)d_in[5];
  void* fn = nullptr;
  cudaDriverEntryPointQueryResult q;
  cudaGetDriverEntryPoint("cuTensorMapEncodeTiled", &fn, cudaEnableDefault, &q);
  EncodeFn enc = (EncodeFn)fn;
  const CUtensorMap tm_x = make_map(enc, x, kD, kS, 64), tm_out = make_map(enc, d_out, kD, kS, 64),
                    tm_wqkv = make_map(enc, wqkv, 3 * kD, kD, 64), tm_wo = make_map(enc, wo, kD, kD, 64),
                    tm_w1 = make_map(enc, w1, kFF, kD, 64), tm_w2 = make_map(enc, w2, kD, kFF, kHS);
  cudaFuncSetAttribute(fused_kernel, cudaFuncAttributeMaxDynamicSharedMemorySize, SM_TOTAL);
  fused_kernel<<<128, 384, SM_TOTAL>>>(tm_x, tm_out, tm_wqkv, tm_wo, tm_w1, tm_w2, wqkv, wo, w1, w2);
}
```

```cpp
#include <cuda_runtime.h>
#include <cuda_bf16.h>
#include <cuda.h>
#include <stdint.h>

#define MAPPING 0
namespace {

constexpr int kS = 2048, kD = 512, kFF = 1376, kHS = 176;
constexpr uint32_t SM_RING = 131072, SLOT = 24576, SM_MISC = 229376;
constexpr uint32_t SM_STAT = SM_MISC;
constexpr uint32_t SM_CS = SM_MISC + 1024;
constexpr uint32_t SM_BAR = SM_CS + 1472;
constexpr uint32_t B_BFULL = SM_BAR, B_BEMPTY = SM_BAR + 32, B_AFULL = SM_BAR + 64  ,
                   B_AFREE = SM_BAR + 192  , B_OWN = SM_BAR + 240  , B_STAT = SM_BAR + 288  ,
                   B_CSRDY = SM_BAR + 304  , B_KVDONE = SM_BAR + 320, B_KVRDY = SM_BAR + 328,
                   B_PRDY = SM_BAR + 336  , B_PFREE = SM_BAR + 352  ;
constexpr uint32_t SM_TOTAL = SM_BAR + 368;
static_assert(SM_TOTAL <= 232448, "smem");
constexpr uint32_t SPIN_LIMIT = 1u << 22;

__device__ uint32_t g_epoch[128 * 8];
__device__ uint32_t g_flags[32 * 8 * 32];
__device__ uint32_t g_cnt[2 * 8 * 32];
__device__ __align__(16) float4 g_cs[8 * 2 * 16 * 48];
__device__ __align__(16) float g_kv[2 * 2 * 8 * 1088];
__device__ __align__(128) float2 g_stats[4 * 32 * 64 * 8];
__device__ __align__(1024) uint4 g_act[3 * 32 * 8 * 512];
__device__ __align__(1024) uint4 g_h[32 * 8 * 3 * 512];
#define STAMP(role, i) do {} while (0)

__device__ __forceinline__ uint32_t smem_u32(const void* p) { return (uint32_t)__cvta_generic_to_shared(p); }
__device__ __forceinline__ void mbar_init(uint32_t bar, uint32_t cnt) { asm volatile("mbarrier.init.shared::cta.b64 [%0], %1;" :: "r"(bar), "r"(cnt)); }
__device__ __forceinline__ void mbar_expect_tx(uint32_t bar, uint32_t bytes) { asm volatile("mbarrier.arrive.expect_tx.shared::cta.b64 _, [%0], %1;" :: "r"(bar), "r"(bytes) : "memory"); }
__device__ __forceinline__ void mbar_arrive(uint32_t bar) { asm volatile("mbarrier.arrive.shared::cta.b64 _, [%0];" :: "r"(bar) : "memory"); }
__device__ __forceinline__ void mbar_arrive_remote(uint32_t bar) { asm volatile("mbarrier.arrive.shared::cluster.b64 _, [%0];" :: "r"(bar) : "memory"); }
__device__ __forceinline__ void mbar_wait(uint32_t bar, uint32_t parity) {
  asm volatile("{\n.reg .pred p;\n.reg .u32 c;\nmov.u32 c, 0;\nWAIT_LOOP:\n"
               "mbarrier.try_wait.parity.shared::cta.b64 p, [%0], %1;\n@p bra WAIT_DONE;\n"
               "add.u32 c, c, 1;\nsetp.lt.u32 p, c, %2;\n@p bra WAIT_LOOP;\ntrap;\nWAIT_DONE:\n}"
               :: "r"(bar), "r"(parity), "n"(SPIN_LIMIT) : "memory");
}
__device__ __forceinline__ uint32_t mapa(uint32_t addr, uint32_t rank) { uint32_t r; asm volatile("mapa.shared::cluster.u32 %0, %1, %2;" : "=r"(r) : "r"(addr), "r"(rank)); return r; }
__device__ __forceinline__ bool elect_one() { uint32_t p; asm volatile("{\n.reg .pred P;\nelect.sync _|P, 0xffffffff;\nselp.u32 %0, 1, 0, P;\n}" : "=r"(p)); return p; }
__device__ __forceinline__ void bulk_g2s(uint32_t dst, const void* src, uint32_t bytes, uint32_t bar) {
  asm volatile("cp.async.bulk.shared::cluster.global.mbarrier::complete_tx::bytes [%0], [%1], %2, [%3];" :: "r"(dst), "l"(src), "r"(bytes), "r"(bar) : "memory");
}
__device__ __forceinline__ void bulk_s2g(void* dst, uint32_t src, uint32_t bytes) { asm volatile("cp.async.bulk.global.shared::cta.bulk_group [%0], [%1], %2;" :: "l"(dst), "r"(src), "r"(bytes) : "memory"); }
__device__ __forceinline__ void bulk_commit() { asm volatile("cp.async.bulk.commit_group;" ::: "memory"); }
template <int N> __device__ __forceinline__ void bulk_wait() { asm volatile("cp.async.bulk.wait_group %0;" :: "n"(N) : "memory"); }
__device__ __forceinline__ void tma_load(uint32_t dst, const CUtensorMap* m, int c0, int c1, uint32_t bar) {
  asm volatile("cp.async.bulk.tensor.2d.shared::cluster.global.mbarrier::complete_tx::bytes [%0], [%1, {%3, %4}], [%2];" :: "r"(dst), "l"(m), "r"(bar), "r"(c0), "r"(c1) : "memory");
}
__device__ __forceinline__ void tma_store(const CUtensorMap* m, uint32_t src, int c0, int c1) {
  asm volatile("cp.async.bulk.tensor.2d.global.shared::cta.bulk_group [%0, {%2, %3}], [%1];" :: "l"(m), "r"(src), "r"(c0), "r"(c1) : "memory");
}
__device__ __forceinline__ void prefetch_l2(const void* p, uint32_t bytes) { asm volatile("cp.async.bulk.prefetch.L2.global [%0], %1;" :: "l"(p), "r"(bytes) : "memory"); }
__device__ __forceinline__ void prefetch_map(const CUtensorMap* m) { asm volatile("prefetch.tensormap [%0];" :: "l"(m) : "memory"); }
__device__ __forceinline__ void fence_async_smem() { asm volatile("fence.proxy.async.shared::cta;" ::: "memory"); }
__device__ __forceinline__ void fence_async_global() { asm volatile("fence.proxy.async.global;" ::: "memory"); }
__device__ __forceinline__ void fence_gpu() { asm volatile("fence.acq_rel.gpu;" ::: "memory"); }
__device__ __forceinline__ void st_release(uint32_t* p, uint32_t v) { asm volatile("st.release.gpu.global.u32 [%0], %1;" :: "l"(p), "r"(v) : "memory"); }
__device__ __forceinline__ uint32_t ld_acquire(const uint32_t* p) { uint32_t v; asm volatile("ld.acquire.gpu.global.u32 %0, [%1];" : "=r"(v) : "l"(p) : "memory"); return v; }
__device__ __forceinline__ uint32_t ld_relaxed(const uint32_t* p) { uint32_t v; asm volatile("ld.relaxed.gpu.global.u32 %0, [%1];" : "=r"(v) : "l"(p) : "memory"); return v; }
__device__ __forceinline__ float2 ld_relaxed_f2(const void* p) { float2 v; asm volatile("ld.relaxed.gpu.global.v2.f32 {%0,%1}, [%2];" : "=f"(v.x), "=f"(v.y) : "l"(p) : "memory"); return v; }
__device__ __forceinline__ float4 ld_relaxed_f4(const void* p) { float4 v; asm volatile("ld.relaxed.gpu.global.v4.f32 {%0,%1,%2,%3}, [%4];" : "=f"(v.x), "=f"(v.y), "=f"(v.z), "=f"(v.w) : "l"(p) : "memory"); return v; }
__device__ __forceinline__ void st_relaxed_b64(void* p, float a, uint32_t b) {
  asm volatile("{\n.reg .b64 v;\nmov.b64 v, {%1, %2};\nst.relaxed.gpu.global.b64 [%0], v;\n}" :: "l"(p), "r"(__float_as_uint(a)), "r"(b) : "memory");
}
__device__ __forceinline__ void red_add_u32(uint32_t* p, uint32_t v) { asm volatile("red.relaxed.gpu.global.add.u32 [%0], %1;" :: "l"(p), "r"(v) : "memory"); }
__device__ __forceinline__ void red_add_f2(float* p, float a, float b) { asm volatile("red.relaxed.gpu.global.add.v2.f32 [%0], {%1, %2};" :: "l"(p), "f"(a), "f"(b) : "memory"); }
__device__ __forceinline__ void red_add_f4(float* p, float a, float b, float c, float d) { asm volatile("red.relaxed.gpu.global.add.v4.f32 [%0], {%1, %2, %3, %4};" :: "l"(p), "f"(a), "f"(b), "f"(c), "f"(d) : "memory"); }
__device__ __forceinline__ void st_async_v4(uint32_t dst, uint32_t a, uint32_t b, uint32_t c, uint32_t d, uint32_t bar) {
  asm volatile("st.async.weak.shared::cluster.mbarrier::complete_tx::bytes.v4.b32 [%0], {%1,%2,%3,%4}, [%5];" :: "r"(dst), "r"(a), "r"(b), "r"(c), "r"(d), "r"(bar) : "memory");
}
__device__ __forceinline__ void stsm4(uint32_t addr, uint32_t a, uint32_t b, uint32_t c, uint32_t d) {
  asm volatile("stmatrix.sync.aligned.m8n8.x4.shared.b16 [%0], {%1,%2,%3,%4};" :: "r"(addr), "r"(a), "r"(b), "r"(c), "r"(d) : "memory");
}
__device__ __forceinline__ void ldsm4(uint32_t addr, uint32_t& a, uint32_t& b, uint32_t& c, uint32_t& d) {
  asm volatile("ldmatrix.sync.aligned.m8n8.x4.shared.b16 {%0,%1,%2,%3}, [%4];" : "=r"(a), "=r"(b), "=r"(c), "=r"(d) : "r"(addr) : "memory");
}
__device__ __forceinline__ void ldsm4t(uint32_t addr, uint32_t& a, uint32_t& b, uint32_t& c, uint32_t& d) {
  asm volatile("ldmatrix.sync.aligned.m8n8.x4.trans.shared.b16 {%0,%1,%2,%3}, [%4];" : "=r"(a), "=r"(b), "=r"(c), "=r"(d) : "r"(addr) : "memory");
}
__device__ __forceinline__ float2 lds_f2(uint32_t addr) { float2 v; asm volatile("ld.shared.v2.f32 {%0,%1}, [%2];" : "=f"(v.x), "=f"(v.y) : "r"(addr) : "memory"); return v; }
__device__ __forceinline__ uint32_t lds_u32(uint32_t addr) { uint32_t v; asm volatile("ld.shared.u32 %0, [%1];" : "=r"(v) : "r"(addr) : "memory"); return v; }
__device__ __forceinline__ void sts_u4(uint32_t addr, uint4 v) { asm volatile("st.shared.v4.u32 [%0], {%1,%2,%3,%4};" :: "r"(addr), "r"(v.x), "r"(v.y), "r"(v.z), "r"(v.w) : "memory"); }
__device__ __forceinline__ uint4 ld_relaxed_u4(const void* p) { uint4 v; asm volatile("ld.relaxed.gpu.global.v4.u32 {%0,%1,%2,%3}, [%4];" : "=r"(v.x), "=r"(v.y), "=r"(v.z), "=r"(v.w) : "l"(p) : "memory"); return v; }
__device__ __forceinline__ void st_relaxed_u32(uint32_t* p, uint32_t v) { asm volatile("st.relaxed.gpu.global.u32 [%0], %1;" :: "l"(p), "r"(v) : "memory"); }
__device__ __forceinline__ void st_relaxed_f4(void* p, float a, float b, float c, uint32_t d) { asm volatile("st.relaxed.gpu.global.v4.b32 [%0], {%1,%2,%3,%4};" :: "l"(p), "r"(__float_as_uint(a)), "r"(__float_as_uint(b)), "r"(__float_as_uint(c)), "r"(d) : "memory"); }
__device__ __forceinline__ uint2 lds_u2(uint32_t addr) { uint2 v; asm volatile("ld.shared.v2.u32 {%0,%1}, [%2];" : "=r"(v.x), "=r"(v.y) : "r"(addr) : "memory"); return v; }
__device__ __forceinline__ uint4 lds_u4(uint32_t addr) { uint4 v; asm volatile("ld.shared.v4.u32 {%0,%1,%2,%3}, [%4];" : "=r"(v.x), "=r"(v.y), "=r"(v.z), "=r"(v.w) : "r"(addr) : "memory"); return v; }
__device__ __forceinline__ void sts_f2(uint32_t addr, float a, float b) { asm volatile("st.shared.v2.f32 [%0], {%1,%2};" :: "r"(addr), "f"(a), "f"(b) : "memory"); }
__device__ __forceinline__ void sts_u2(uint32_t addr, uint32_t a, uint32_t b) { asm volatile("st.shared.v2.u32 [%0], {%1,%2};" :: "r"(addr), "r"(a), "r"(b) : "memory"); }
__device__ __forceinline__ void sts_f4(uint32_t addr, float4 v) { asm volatile("st.shared.v4.f32 [%0], {%1,%2,%3,%4};" :: "r"(addr), "f"(v.x), "f"(v.y), "f"(v.z), "f"(v.w) : "memory"); }
__device__ __forceinline__ void mma16816(float (&c)[4], uint32_t a0, uint32_t a1, uint32_t a2, uint32_t a3, uint32_t b0, uint32_t b1) {
  asm volatile("mma.sync.aligned.m16n8k16.row.col.f32.bf16.bf16.f32 {%0,%1,%2,%3}, {%4,%5,%6,%7}, {%8,%9}, {%0,%1,%2,%3};"
               : "+f"(c[0]), "+f"(c[1]), "+f"(c[2]), "+f"(c[3]) : "r"(a0), "r"(a1), "r"(a2), "r"(a3), "r"(b0), "r"(b1));
}
__device__ __forceinline__ uint32_t pack_bf16(float lo, float hi) { uint32_t r; asm("cvt.rn.bf16x2.f32 %0, %1, %2;" : "=r"(r) : "f"(hi), "f"(lo)); return r; }
__device__ __forceinline__ uint32_t pack_bf16_relu(float lo, float hi) { uint32_t r; asm("cvt.rn.relu.bf16x2.f32 %0, %1, %2;" : "=r"(r) : "f"(hi), "f"(lo)); return r; }
__device__ __forceinline__ float bf_lo(uint32_t v) { return __uint_as_float(v << 16); }
__device__ __forceinline__ float bf_hi(uint32_t v) { return __uint_as_float(v & 0xffff0000u); }
__device__ __forceinline__ float ex2(float x) { float y; asm("ex2.approx.ftz.f32 %0, %1;" : "=f"(y) : "f"(x)); return y; }
__device__ __forceinline__ float rcp(float x) { float y; asm("rcp.approx.ftz.f32 %0, %1;" : "=f"(y) : "f"(x)); return y; }
__device__ __forceinline__ float phi_y(float y) { return fmaf(fmaxf(y, 1.4426950408889634e-6f), 0.6931471805599453f, ex2(fminf(y, 0.f))); }
__device__ __forceinline__ int opaque(int x) { int y; asm volatile("mov.u32 %0, %1;" : "=r"(y) : "r"(x)); return y; }
__device__ __forceinline__ void wg_fence() { asm volatile("wgmma.fence.sync.aligned;" ::: "memory"); }
__device__ __forceinline__ void wg_commit() { asm volatile("wgmma.commit_group.sync.aligned;" ::: "memory"); }
template <int N> __device__ __forceinline__ void wg_wait() { asm volatile("wgmma.wait_group.sync.aligned %0;" :: "n"(N) : "memory"); }
template <int N> __device__ __forceinline__ void fence_regs(float (&d)[N]) {
#pragma unroll
  for (int i = 0; i < N; i++) asm volatile("" : "+f"(d[i]) :: "memory");
}
template <int N> __device__ __forceinline__ void zero_regs(float (&d)[N]) {
#pragma unroll
  for (int i = 0; i < N; i++) d[i] = 0.f;
  fence_regs(d);
}
__device__ __forceinline__ void wg_bar(int wg) { if (wg == 0) asm volatile("bar.sync 1, 128;" ::: "memory"); else asm volatile("bar.sync 2, 128;" ::: "memory"); }
__device__ __forceinline__ uint32_t desc_lo(uint32_t addr, uint32_t lbo) { return ((addr & 0x3FFFF) >> 4) | ((lbo >> 4) << 16); }
constexpr uint32_t HI_SW = 0x40000040u;
constexpr uint32_t HI_NS = 0x00000008u;
template <int I> struct IC { static constexpr int value = I; };
template <int B, int E, class F> __device__ __forceinline__ void static_for(F&& f) {
  if constexpr (B < E) { f(IC<B>{}); static_for<B + 1, E>(f); }
}

template <int OA, int OB, uint32_t HA>
__device__ __forceinline__ void wgmma_n64_init(float (&d)[32], uint32_t la, uint32_t lb) {
  asm volatile("{\n.reg .pred p;\n.reg .b32 ta, tb;\n.reg .b64 da, db;\n"
    "setp.ne.b32 p, 0, 0;\nadd.u32 ta, %32, %34;\nadd.u32 tb, %33, %35;\n"
    "mov.b64 da, {ta, %36};\nmov.b64 db, {tb, 0x40000040};\n"
    "wgmma.mma_async.sync.aligned.m64n64k16.f32.bf16.bf16 "
    "{%0, %1, %2, %3, %4, %5, %6, %7, %8, %9, %10, %11, %12, %13, %14, %15, "
    "%16, %17, %18, %19, %20, %21, %22, %23, %24, %25, %26, %27, %28, %29, %30, %31}, "
    "da, db, p, 1, 1, 0, 1;\n}"
    : "=f"(d[0]), "=f"(d[1]), "=f"(d[2]), "=f"(d[3]), "=f"(d[4]), "=f"(d[5]), "=f"(d[6]), "=f"(d[7]),
      "=f"(d[8]), "=f"(d[9]), "=f"(d[10]), "=f"(d[11]), "=f"(d[12]), "=f"(d[13]), "=f"(d[14]), "=f"(d[15]),
      "=f"(d[16]), "=f"(d[17]), "=f"(d[18]), "=f"(d[19]), "=f"(d[20]), "=f"(d[21]), "=f"(d[22]), "=f"(d[23]),
      "=f"(d[24]), "=f"(d[25]), "=f"(d[26]), "=f"(d[27]), "=f"(d[28]), "=f"(d[29]), "=f"(d[30]), "=f"(d[31])
    : "r"(la), "r"(lb), "n"(OA), "n"(OB), "n"(HA));
}
template <int OA, int OB, uint32_t HA>
__device__ __forceinline__ void wgmma_n128_init(float (&d)[32], float (&e)[32], uint32_t la, uint32_t lb) {
  asm volatile("{\n.reg .pred p;\n.reg .b32 ta, tb;\n.reg .b64 da, db;\n"
    "setp.ne.b32 p, 0, 0;\nadd.u32 ta, %64, %66;\nadd.u32 tb, %65, %67;\n"
    "mov.b64 da, {ta, %68};\nmov.b64 db, {tb, 0x40000040};\n"
    "wgmma.mma_async.sync.aligned.m64n128k16.f32.bf16.bf16 "
    "{%0, %1, %2, %3, %4, %5, %6, %7, %8, %9, %10, %11, %12, %13, %14, %15, "
    "%16, %17, %18, %19, %20, %21, %22, %23, %24, %25, %26, %27, %28, %29, %30, %31, "
    "%32, %33, %34, %35, %36, %37, %38, %39, %40, %41, %42, %43, %44, %45, %46, %47, "
    "%48, %49, %50, %51, %52, %53, %54, %55, %56, %57, %58, %59, %60, %61, %62, %63}, "
    "da, db, p, 1, 1, 0, 1;\n}"
    : "=f"(d[0]), "=f"(d[1]), "=f"(d[2]), "=f"(d[3]), "=f"(d[4]), "=f"(d[5]), "=f"(d[6]), "=f"(d[7]),
      "=f"(d[8]), "=f"(d[9]), "=f"(d[10]), "=f"(d[11]), "=f"(d[12]), "=f"(d[13]), "=f"(d[14]), "=f"(d[15]),
      "=f"(d[16]), "=f"(d[17]), "=f"(d[18]), "=f"(d[19]), "=f"(d[20]), "=f"(d[21]), "=f"(d[22]), "=f"(d[23]),
      "=f"(d[24]), "=f"(d[25]), "=f"(d[26]), "=f"(d[27]), "=f"(d[28]), "=f"(d[29]), "=f"(d[30]), "=f"(d[31]),
      "=f"(e[0]), "=f"(e[1]), "=f"(e[2]), "=f"(e[3]), "=f"(e[4]), "=f"(e[5]), "=f"(e[6]), "=f"(e[7]),
      "=f"(e[8]), "=f"(e[9]), "=f"(e[10]), "=f"(e[11]), "=f"(e[12]), "=f"(e[13]), "=f"(e[14]), "=f"(e[15]),
      "=f"(e[16]), "=f"(e[17]), "=f"(e[18]), "=f"(e[19]), "=f"(e[20]), "=f"(e[21]), "=f"(e[22]), "=f"(e[23]),
      "=f"(e[24]), "=f"(e[25]), "=f"(e[26]), "=f"(e[27]), "=f"(e[28]), "=f"(e[29]), "=f"(e[30]), "=f"(e[31])
    : "r"(la), "r"(lb), "n"(OA), "n"(OB), "n"(HA));
}
template <int OA, int OB, uint32_t HA>
__device__ __forceinline__ void wgmma_n176_init(float (&d)[88], uint32_t la, uint32_t lb) {
  asm volatile("{\n.reg .pred p;\n.reg .b32 ta, tb;\n.reg .b64 da, db;\n"
    "setp.ne.b32 p, 0, 0;\nadd.u32 ta, %88, %90;\nadd.u32 tb, %89, %91;\n"
    "mov.b64 da, {ta, %92};\nmov.b64 db, {tb, 0x40000040};\n"
    "wgmma.mma_async.sync.aligned.m64n176k16.f32.bf16.bf16 "
    "{%0, %1, %2, %3, %4, %5, %6, %7, %8, %9, %10, %11, %12, %13, %14, %15, "
    "%16, %17, %18, %19, %20, %21, %22, %23, %24, %25, %26, %27, %28, %29, %30, %31, "
    "%32, %33, %34, %35, %36, %37, %38, %39, %40, %41, %42, %43, %44, %45, %46, %47, "
    "%48, %49, %50, %51, %52, %53, %54, %55, %56, %57, %58, %59, %60, %61, %62, %63, "
    "%64, %65, %66, %67, %68, %69, %70, %71, %72, %73, %74, %75, %76, %77, %78, %79, "
    "%80, %81, %82, %83, %84, %85, %86, %87}, "
    "da, db, p, 1, 1, 0, 1;\n}"
    : "=f"(d[0]), "=f"(d[1]), "=f"(d[2]), "=f"(d[3]), "=f"(d[4]), "=f"(d[5]), "=f"(d[6]), "=f"(d[7]),
      "=f"(d[8]), "=f"(d[9]), "=f"(d[10]), "=f"(d[11]), "=f"(d[12]), "=f"(d[13]), "=f"(d[14]), "=f"(d[15]),
      "=f"(d[16]), "=f"(d[17]), "=f"(d[18]), "=f"(d[19]), "=f"(d[20]), "=f"(d[21]), "=f"(d[22]), "=f"(d[23]),
      "=f"(d[24]), "=f"(d[25]), "=f"(d[26]), "=f"(d[27]), "=f"(d[28]), "=f"(d[29]), "=f"(d[30]), "=f"(d[31]),
      "=f"(d[32]), "=f"(d[33]), "=f"(d[34]), "=f"(d[35]), "=f"(d[36]), "=f"(d[37]), "=f"(d[38]), "=f"(d[39]),
      "=f"(d[40]), "=f"(d[41]), "=f"(d[42]), "=f"(d[43]), "=f"(d[44]), "=f"(d[45]), "=f"(d[46]), "=f"(d[47]),
      "=f"(d[48]), "=f"(d[49]), "=f"(d[50]), "=f"(d[51]), "=f"(d[52]), "=f"(d[53]), "=f"(d[54]), "=f"(d[55]),
      "=f"(d[56]), "=f"(d[57]), "=f"(d[58]), "=f"(d[59]), "=f"(d[60]), "=f"(d[61]), "=f"(d[62]), "=f"(d[63]),
      "=f"(d[64]), "=f"(d[65]), "=f"(d[66]), "=f"(d[67]), "=f"(d[68]), "=f"(d[69]), "=f"(d[70]), "=f"(d[71]),
      "=f"(d[72]), "=f"(d[73]), "=f"(d[74]), "=f"(d[75]), "=f"(d[76]), "=f"(d[77]), "=f"(d[78]), "=f"(d[79]),
      "=f"(d[80]), "=f"(d[81]), "=f"(d[82]), "=f"(d[83]), "=f"(d[84]), "=f"(d[85]), "=f"(d[86]), "=f"(d[87])
    : "r"(la), "r"(lb), "n"(OA), "n"(OB), "n"(HA));
}
template <int OA, int OB, uint32_t HA>
__device__ __forceinline__ void wgmma_n64(float (&d)[32], uint32_t la, uint32_t lb) {
  asm volatile("{\n.reg .pred p;\n.reg .b32 ta, tb;\n.reg .b64 da, db;\n"
    "setp.eq.b32 p, 0, 0;\nadd.u32 ta, %32, %34;\nadd.u32 tb, %33, %35;\n"
    "mov.b64 da, {ta, %36};\nmov.b64 db, {tb, 0x40000040};\n"
    "wgmma.mma_async.sync.aligned.m64n64k16.f32.bf16.bf16 "
    "{%0, %1, %2, %3, %4, %5, %6, %7, %8, %9, %10, %11, %12, %13, %14, %15, "
    "%16, %17, %18, %19, %20, %21, %22, %23, %24, %25, %26, %27, %28, %29, %30, %31}, "
    "da, db, p, 1, 1, 0, 1;\n}"
    : "+f"(d[0]), "+f"(d[1]), "+f"(d[2]), "+f"(d[3]), "+f"(d[4]), "+f"(d[5]), "+f"(d[6]), "+f"(d[7]),
      "+f"(d[8]), "+f"(d[9]), "+f"(d[10]), "+f"(d[11]), "+f"(d[12]), "+f"(d[13]), "+f"(d[14]), "+f"(d[15]),
      "+f"(d[16]), "+f"(d[17]), "+f"(d[18]), "+f"(d[19]), "+f"(d[20]), "+f"(d[21]), "+f"(d[22]), "+f"(d[23]),
      "+f"(d[24]), "+f"(d[25]), "+f"(d[26]), "+f"(d[27]), "+f"(d[28]), "+f"(d[29]), "+f"(d[30]), "+f"(d[31])
    : "r"(la), "r"(lb), "n"(OA), "n"(OB), "n"(HA));
}
template <int OA, int OB, uint32_t HA>
__device__ __forceinline__ void wgmma_n128(float (&d)[32], float (&e)[32], uint32_t la, uint32_t lb) {
  asm volatile("{\n.reg .pred p;\n.reg .b32 ta, tb;\n.reg .b64 da, db;\n"
    "setp.eq.b32 p, 0, 0;\nadd.u32 ta, %64, %66;\nadd.u32 tb, %65, %67;\n"
    "mov.b64 da, {ta, %68};\nmov.b64 db, {tb, 0x40000040};\n"
    "wgmma.mma_async.sync.aligned.m64n128k16.f32.bf16.bf16 "
    "{%0, %1, %2, %3, %4, %5, %6, %7, %8, %9, %10, %11, %12, %13, %14, %15, "
    "%16, %17, %18, %19, %20, %21, %22, %23, %24, %25, %26, %27, %28, %29, %30, %31, "
    "%32, %33, %34, %35, %36, %37, %38, %39, %40, %41, %42, %43, %44, %45, %46, %47, "
    "%48, %49, %50, %51, %52, %53, %54, %55, %56, %57, %58, %59, %60, %61, %62, %63}, "
    "da, db, p, 1, 1, 0, 1;\n}"
    : "+f"(d[0]), "+f"(d[1]), "+f"(d[2]), "+f"(d[3]), "+f"(d[4]), "+f"(d[5]), "+f"(d[6]), "+f"(d[7]),
      "+f"(d[8]), "+f"(d[9]), "+f"(d[10]), "+f"(d[11]), "+f"(d[12]), "+f"(d[13]), "+f"(d[14]), "+f"(d[15]),
      "+f"(d[16]), "+f"(d[17]), "+f"(d[18]), "+f"(d[19]), "+f"(d[20]), "+f"(d[21]), "+f"(d[22]), "+f"(d[23]),
      "+f"(d[24]), "+f"(d[25]), "+f"(d[26]), "+f"(d[27]), "+f"(d[28]), "+f"(d[29]), "+f"(d[30]), "+f"(d[31]),
      "+f"(e[0]), "+f"(e[1]), "+f"(e[2]), "+f"(e[3]), "+f"(e[4]), "+f"(e[5]), "+f"(e[6]), "+f"(e[7]),
      "+f"(e[8]), "+f"(e[9]), "+f"(e[10]), "+f"(e[11]), "+f"(e[12]), "+f"(e[13]), "+f"(e[14]), "+f"(e[15]),
      "+f"(e[16]), "+f"(e[17]), "+f"(e[18]), "+f"(e[19]), "+f"(e[20]), "+f"(e[21]), "+f"(e[22]), "+f"(e[23]),
      "+f"(e[24]), "+f"(e[25]), "+f"(e[26]), "+f"(e[27]), "+f"(e[28]), "+f"(e[29]), "+f"(e[30]), "+f"(e[31])
    : "r"(la), "r"(lb), "n"(OA), "n"(OB), "n"(HA));
}
template <int OA, int OB, uint32_t HA>
__device__ __forceinline__ void wgmma_n176(float (&d)[88], uint32_t la, uint32_t lb) {
  asm volatile("{\n.reg .pred p;\n.reg .b32 ta, tb;\n.reg .b64 da, db;\n"
    "setp.eq.b32 p, 0, 0;\nadd.u32 ta, %88, %90;\nadd.u32 tb, %89, %91;\n"
    "mov.b64 da, {ta, %92};\nmov.b64 db, {tb, 0x40000040};\n"
    "wgmma.mma_async.sync.aligned.m64n176k16.f32.bf16.bf16 "
    "{%0, %1, %2, %3, %4, %5, %6, %7, %8, %9, %10, %11, %12, %13, %14, %15, "
    "%16, %17, %18, %19, %20, %21, %22, %23, %24, %25, %26, %27, %28, %29, %30, %31, "
    "%32, %33, %34, %35, %36, %37, %38, %39, %40, %41, %42, %43, %44, %45, %46, %47, "
    "%48, %49, %50, %51, %52, %53, %54, %55, %56, %57, %58, %59, %60, %61, %62, %63, "
    "%64, %65, %66, %67, %68, %69, %70, %71, %72, %73, %74, %75, %76, %77, %78, %79, "
    "%80, %81, %82, %83, %84, %85, %86, %87}, "
    "da, db, p, 1, 1, 0, 1;\n}"
    : "+f"(d[0]), "+f"(d[1]), "+f"(d[2]), "+f"(d[3]), "+f"(d[4]), "+f"(d[5]), "+f"(d[6]), "+f"(d[7]),
      "+f"(d[8]), "+f"(d[9]), "+f"(d[10]), "+f"(d[11]), "+f"(d[12]), "+f"(d[13]), "+f"(d[14]), "+f"(d[15]),
      "+f"(d[16]), "+f"(d[17]), "+f"(d[18]), "+f"(d[19]), "+f"(d[20]), "+f"(d[21]), "+f"(d[22]), "+f"(d[23]),
      "+f"(d[24]), "+f"(d[25]), "+f"(d[26]), "+f"(d[27]), "+f"(d[28]), "+f"(d[29]), "+f"(d[30]), "+f"(d[31]),
      "+f"(d[32]), "+f"(d[33]), "+f"(d[34]), "+f"(d[35]), "+f"(d[36]), "+f"(d[37]), "+f"(d[38]), "+f"(d[39]),
      "+f"(d[40]), "+f"(d[41]), "+f"(d[42]), "+f"(d[43]), "+f"(d[44]), "+f"(d[45]), "+f"(d[46]), "+f"(d[47]),
      "+f"(d[48]), "+f"(d[49]), "+f"(d[50]), "+f"(d[51]), "+f"(d[52]), "+f"(d[53]), "+f"(d[54]), "+f"(d[55]),
      "+f"(d[56]), "+f"(d[57]), "+f"(d[58]), "+f"(d[59]), "+f"(d[60]), "+f"(d[61]), "+f"(d[62]), "+f"(d[63]),
      "+f"(d[64]), "+f"(d[65]), "+f"(d[66]), "+f"(d[67]), "+f"(d[68]), "+f"(d[69]), "+f"(d[70]), "+f"(d[71]),
      "+f"(d[72]), "+f"(d[73]), "+f"(d[74]), "+f"(d[75]), "+f"(d[76]), "+f"(d[77]), "+f"(d[78]), "+f"(d[79]),
      "+f"(d[80]), "+f"(d[81]), "+f"(d[82]), "+f"(d[83]), "+f"(d[84]), "+f"(d[85]), "+f"(d[86]), "+f"(d[87])
    : "r"(la), "r"(lb), "n"(OA), "n"(OB), "n"(HA));
}

__device__ __forceinline__ void publish_stats(const uint32_t (&xr)[16], float2* dst  , int t, uint32_t tag) {
  float s0 = 0.f, s1 = 0.f;
#pragma unroll
  for (int j = 0; j < 8; j++) { s0 += bf_lo(xr[2 * j]) + bf_hi(xr[2 * j]); s1 += bf_lo(xr[2 * j + 1]) + bf_hi(xr[2 * j + 1]); }
  s0 += __shfl_xor_sync(0xffffffff, s0, 1); s1 += __shfl_xor_sync(0xffffffff, s1, 1);
  s0 += __shfl_xor_sync(0xffffffff, s0, 2); s1 += __shfl_xor_sync(0xffffffff, s1, 2);
  const float m0 = s0 * (1.f / 64.f), m1 = s1 * (1.f / 64.f);
  float q0 = 0.f, q1 = 0.f;
#pragma unroll
  for (int j = 0; j < 8; j++) {
    float a = bf_lo(xr[2 * j]) - m0, b = bf_hi(xr[2 * j]) - m0, c = bf_lo(xr[2 * j + 1]) - m1, d = bf_hi(xr[2 * j + 1]) - m1;
    q0 = fmaf(a, a, q0); q0 = fmaf(b, b, q0); q1 = fmaf(c, c, q1); q1 = fmaf(d, d, q1);
  }
  q0 += __shfl_xor_sync(0xffffffff, q0, 1); q1 += __shfl_xor_sync(0xffffffff, q1, 1);
  q0 += __shfl_xor_sync(0xffffffff, q0, 2); q1 += __shfl_xor_sync(0xffffffff, q1, 2);
  if (t < 2) st_relaxed_b64(dst + 8 * t, t ? s1 : s0, (__float_as_uint(t ? q1 : q0) & ~1u) | tag);
}

__device__ __forceinline__ void gather_stats(const float2* src  , uint32_t sm_dst, uint32_t bar, int lane, uint32_t tag) {
  const float2* p = src + lane * 2;
  float4 v[8];
  uint32_t cnt = 0;
  while (true) {
#pragma unroll
    for (int i = 0; i < 8; i++) v[i] = ld_relaxed_f4(p + i * 64);
    uint32_t bad = 0;
#pragma unroll
    for (int i = 0; i < 8; i++) bad |= (__float_as_uint(v[i].y) ^ tag) | (__float_as_uint(v[i].w) ^ tag);
    if (__all_sync(0xffffffff, (bad & 1u) == 0)) break;
    if (++cnt > SPIN_LIMIT) __trap();
    __nanosleep(100);
  }
  float sa = 0.f, sb = 0.f, qa = 0.f, qb = 0.f;
#pragma unroll
  for (int i = 0; i < 8; i++) { sa += v[i].x; qa += v[i].y; sb += v[i].z; qb += v[i].w; }
  const float ma = sa * (1.f / 512.f), mb = sb * (1.f / 512.f);
  float da = 0.f, db = 0.f;
#pragma unroll
  for (int i = 0; i < 8; i++) {
    const float a = v[i].x * (1.f / 64.f) - ma, b = v[i].z * (1.f / 64.f) - mb;
    da = fmaf(a, a, da); db = fmaf(b, b, db);
  }
  sts_f4(sm_dst + lane * 16, make_float4(rsqrtf(fmaf(da, 64.f, qa) * (1.f / 512.f) + 1e-5f), -ma, rsqrtf(fmaf(db, 64.f, qb) * (1.f / 512.f) + 1e-5f), -mb));
  __syncwarp();
  if (lane == 0) mbar_arrive(bar);
}

__device__ __forceinline__ void colsum_task(const __nv_bfloat16* p  , int pitch, bool ok, int row0, float4* dst  , int lane, uint32_t tag) {
  const int rg = lane >> 3;
  float a[8];
#pragma unroll
  for (int i = 0; i < 8; i++) a[i] = 0.f;
  if (ok) {
    uint4 v[8];
#pragma unroll
    for (int i = 0; i < 8; i++) v[i] = __ldg((const uint4*)(p + (size_t)(row0 + 4 * i + rg) * pitch));
#pragma unroll
    for (int i = 0; i < 8; i++) {
      a[0] += bf_lo(v[i].x); a[1] += bf_hi(v[i].x); a[2] += bf_lo(v[i].y); a[3] += bf_hi(v[i].y);
      a[4] += bf_lo(v[i].z); a[5] += bf_hi(v[i].z); a[6] += bf_lo(v[i].w); a[7] += bf_hi(v[i].w);
    }
  }
#pragma unroll
  for (int i = 0; i < 8; i++) { a[i] += __shfl_xor_sync(0xffffffff, a[i], 8); a[i] += __shfl_xor_sync(0xffffffff, a[i], 16); }
  if (rg == 0) {
    st_relaxed_f4(dst, a[0], a[1], a[2], (__float_as_uint(a[3]) & ~1u) | tag);
    st_relaxed_f4(dst + 1, a[4], a[5], a[6], (__float_as_uint(a[7]) & ~1u) | tag);
  }
}
__device__ __forceinline__ void colsum_gather(const float4* src, uint32_t sm_dst, int nunits, uint32_t bar, int lane, uint32_t tag) {
#pragma unroll 1
  for (int j = 0; j < 3; j++) {
    const float4* p = src + (lane >> 4) * 8 * 48 + j * 16 + (lane & 15);
    float4 v[8];
    uint32_t cnt = 0;
    while (true) {
      uint32_t bad = 0;
#pragma unroll
      for (int i = 0; i < 8; i++) v[i] = ld_relaxed_f4(p + i * 48);
#pragma unroll
      for (int i = 0; i < 8; i++) bad |= __float_as_uint(v[i].w) ^ tag;
      if (__all_sync(0xffffffff, (bad & 1u) == 0)) break;
      if (++cnt > SPIN_LIMIT) __trap();
    }
    float4 a = v[0];
#pragma unroll
    for (int i = 1; i < 8; i++) { a.x += v[i].x; a.y += v[i].y; a.z += v[i].z; a.w += v[i].w; }
    a.x += __shfl_xor_sync(0xffffffff, a.x, 16); a.y += __shfl_xor_sync(0xffffffff, a.y, 16);
    a.z += __shfl_xor_sync(0xffffffff, a.z, 16); a.w += __shfl_xor_sync(0xffffffff, a.w, 16);
    if (lane < 16 && j * 16 + lane < nunits) sts_f4(sm_dst + (j * 16 + lane) * 16, a);
  }
  __syncwarp();
  if (lane == 0) mbar_arrive(bar);
}

__device__ __forceinline__ void wait_flag_acq(const uint32_t* f, uint32_t ev) {
  uint32_t cnt = 0;
  while ((int32_t)(ld_acquire(f) - ev) < 0) { if (++cnt > SPIN_LIMIT) __trap(); }
}
__device__ __forceinline__ void wait_flags(const uint32_t* f  , uint32_t ev) {
  uint32_t cnt = 0;
  while (!__all_sync(0xffffffff, (int32_t)(ld_relaxed(f) - ev) >= 0)) { if (++cnt > SPIN_LIMIT) __trap(); }
}
__device__ __forceinline__ void publish_chunk(uint4* gdst, uint32_t src, uint32_t* flag, uint32_t ev, int lane) {
  if (lane == 0) { bulk_s2g(gdst, src, 8192); bulk_commit(); bulk_wait<0>(); }
  __syncwarp();
  if (lane < 8) st_relaxed_u32(flag + lane * 32, ev);
}
__device__ __forceinline__ void fetch_chunks(const uint4* gbuf  , const uint32_t* flags, uint32_t abase, uint32_t afull, int r, uint32_t ev, int lane) {
  wait_flags(flags + r * 32 + (lane & 7), ev);
  if (elect_one()) {
#pragma unroll
    for (int i = 1; i < 8; i++) {
      mbar_expect_tx(afull + i * 8, 8192);
      bulk_g2s(abase + i * 8192, gbuf + ((r + i) & 7) * 512, 8192, afull + i * 8);
    }
  }
  __syncwarp();
}

__global__ void __cluster_dims__(2, 1, 1) __launch_bounds__(384, 1)
fused_kernel(const __grid_constant__ CUtensorMap tm_x, const __grid_constant__ CUtensorMap tm_out,
             const __grid_constant__ CUtensorMap tm_wqkv, const __grid_constant__ CUtensorMap tm_wo,
             const __grid_constant__ CUtensorMap tm_w1, const __grid_constant__ CUtensorMap tm_w2,
             const __nv_bfloat16* __restrict__ wqkv, const __nv_bfloat16* __restrict__ wo,
             const __nv_bfloat16* __restrict__ w1, const __nv_bfloat16* __restrict__ w2) {
  extern __shared__ __align__(1024) uint8_t smem_raw[];
  const uint32_t sb = smem_u32(smem_raw);
  const int warp = __shfl_sync(0xffffffff, threadIdx.x >> 5, 0);
  const int bid = __shfl_sync(0xffffffff, opaque(blockIdx.x), 0);
  int cb, r;
  {
    const int cl = bid >> 1;
    cb = cl >> 2; r = (cl & 3) * 2 + (bid & 1);
  }

  const int prof_id = cb * 8 + r; (void)prof_id;
  if (threadIdx.x == 0) {
    if (sb & 1023) __trap();
    for (int i = 0; i < 4; i++) { mbar_init(sb + B_BFULL + i * 8, 1); mbar_init(sb + B_BEMPTY + i * 8, 8); }
    for (int i = 0; i < 16; i++) mbar_init(sb + B_AFULL + i * 8, 1);
    for (int i = 0; i < 6; i++) { mbar_init(sb + B_AFREE + i * 8, 4); mbar_init(sb + B_OWN + i * 8, 4); }
    for (int i = 0; i < 2; i++) { mbar_init(sb + B_STAT + i * 8, 1); mbar_init(sb + B_PRDY + i * 8, 1); mbar_init(sb + B_PFREE + i * 8, 4); }
    mbar_init(sb + B_CSRDY, 1); mbar_init(sb + B_CSRDY + 8, 1); mbar_init(sb + B_KVDONE, 8); mbar_init(sb + B_KVRDY, 1);
    asm volatile("fence.mbarrier_init.release.cluster;" ::: "memory");
  }
  __syncthreads();
  asm volatile("barrier.cluster.arrive.relaxed.aligned;" ::: "memory");

  if (warp >= 8) {
  asm volatile("setmaxnreg.dec.sync.aligned.u32 96;");
  const int lane = __shfl_sync(0xffffffff, threadIdx.x & 31, threadIdx.x & 31);
  const uint32_t epoch = ld_relaxed(g_epoch + bid * 8);
  if (warp == 8) {
    uint32_t st = 0;
    auto acquire = [&](uint32_t bytes) -> uint32_t {
      const uint32_t s = st & 3;
      mbar_wait(sb + B_BEMPTY + s * 8, ((st >> 2) & 1) ^ 1);
      st++;
      return s;
    };
    if (lane == 0) { prefetch_map(&tm_wqkv); prefetch_map(&tm_wo); prefetch_map(&tm_w1); prefetch_map(&tm_w2); }
#pragma unroll 1
    for (int l = 0; l < 2; l++) {
#pragma unroll 1
      for (int i = 0; i < 8; i++) {
        const uint32_t s = acquire(0), dst = sb + SM_RING + s * SLOT, fb = sb + B_BFULL + s * 8;
        const int kc = (r + i) & 7;
        if (elect_one()) { mbar_expect_tx(fb, 16384); tma_load(dst, &tm_wqkv, 512 + 64 * r, 64 * kc, fb); tma_load(dst + 8192, &tm_wqkv, 1024 + 64 * r, 64 * kc, fb); }
      }
#pragma unroll 1
      for (int i = 0; i < 4; i++) {
        const uint32_t s = acquire(0), dst = sb + SM_RING + s * SLOT, fb = sb + B_BFULL + s * 8;
        if (elect_one()) { mbar_expect_tx(fb, 16384); tma_load(dst, &tm_wqkv, 64 * r, 64 * ((r + 2 * i) & 7), fb); tma_load(dst + 8192, &tm_wqkv, 64 * r, 64 * ((r + 2 * i + 1) & 7), fb); }
      }
#pragma unroll 1
      for (int i = 0; i < 4; i++) {
        const uint32_t s = acquire(0), dst = sb + SM_RING + s * SLOT, fb = sb + B_BFULL + s * 8;
        if (elect_one()) { mbar_expect_tx(fb, 16384); tma_load(dst, &tm_wo, 64 * r, 64 * ((r + 2 * i) & 7), fb); tma_load(dst + 8192, &tm_wo, 64 * r, 64 * ((r + 2 * i + 1) & 7), fb); }
      }
#pragma unroll 1
      for (int i = 0; i < 8; i++) {
        const uint32_t s = acquire(0), dst = sb + SM_RING + s * SLOT, fb = sb + B_BFULL + s * 8;
        const int kc = (r + i) & 7;
        if (elect_one()) { mbar_expect_tx(fb, 24576); tma_load(dst, &tm_w1, kHS * r, 64 * kc, fb); tma_load(dst + 8192, &tm_w1, kHS * r + 64, 64 * kc, fb); tma_load(dst + 16384, &tm_w1, kHS * r + 128, 64 * kc, fb); }
      }
#pragma unroll 1
      for (int i = 0; i < 8; i++) {
        const uint32_t s = acquire(0), dst = sb + SM_RING + s * SLOT, fb = sb + B_BFULL + s * 8;
        const int j = (r + (i & ~1)) & 7;
        if (elect_one()) { mbar_expect_tx(fb, kHS * 128); tma_load(dst, &tm_w2, 64 * ((i & 1) ? r : (r ^ 1)), kHS * j, fb); }
      }
    }
    asm volatile("barrier.cluster.wait.aligned;" ::: "memory");
  } else if (warp == 9 || warp == 10) {
    const int h = warp - 9, half0 = cb * 2 + h;
    if (elect_one()) {
      const uint32_t abase = sb + h * 65536, afull = sb + B_AFULL + h * 64;
      prefetch_map(&tm_x);
      for (int i = 0; i < 8; i++) { mbar_expect_tx(afull + i * 8, 8192); tma_load(abase + i * 8192, &tm_x, 64 * ((r + i) & 7), 128 * cb + 64 * h, afull + i * 8); }
    }
    __syncwarp();
    const uint32_t ev0 = epoch * 16, tag = (epoch + 1) & 1;
    colsum_task(wqkv + (1 + h) * 512 + 64 * r + 8 * (lane & 7), 3 * kD, true, 32 * cb, g_cs + ((r * 2 + 0) * 16 + cb) * 48 + (1 + h) * 16 + 2 * (lane & 7), lane, tag);
    gather_stats(g_stats + (0 * 32 + half0) * 512, sb + SM_STAT + h * 512, sb + B_STAT + h * 8, lane, tag);
#pragma unroll 1
    for (int b = h; b < 3; b += 2) {
      const int col = 64 * b + 8 * (lane & 7);
      colsum_task(w1 + kHS * r + col, kFF, col < kHS && kHS * r + col < kFF, 32 * cb, g_cs + ((r * 2 + 1) * 16 + cb) * 48 + b * 16 + 2 * (lane & 7), lane, tag);
    }
    asm volatile("barrier.cluster.wait.aligned;" ::: "memory");
    uint32_t p0 = 0;
#pragma unroll 1
    for (int l = 0; l < 2; l++) {
      const uint32_t ev = ev0 + l * 6;
      const int half = opaque(half0);
      const uint32_t abase = sb + h * 65536, afull = sb + B_AFULL + h * 64, afree = sb + B_AFREE + h * 24, own = sb + B_OWN + h * 24;
      uint32_t* flags = g_flags + half * 256;
      mbar_wait(own, p0);
      STAMP(2 + h, l * 16 + 0);
      publish_chunk(g_act + (0 * 32 + half) * 4096 + r * 512, abase, flags + r, ev + 1, lane);
      STAMP(2 + h, l * 16 + 11);
      mbar_wait(afree, p0); p0 ^= 1;
      fetch_chunks(g_act + (0 * 32 + half) * 4096, flags, abase, afull, r, ev + 1, lane);
      STAMP(2 + h, l * 16 + 1);
      mbar_wait(own, p0);
      STAMP(2 + h, l * 16 + 2);
      publish_chunk(g_act + (1 * 32 + half) * 4096 + r * 512, abase, flags + r, ev + 2, lane);
      mbar_wait(afree, p0); p0 ^= 1;
      STAMP(2 + h, l * 16 + 12);
      fetch_chunks(g_act + (1 * 32 + half) * 4096, flags, abase, afull, r, ev + 2, lane);
      STAMP(2 + h, l * 16 + 4);
      gather_stats(g_stats + ((2 * l + 1) * 32 + half) * 512, sb + SM_STAT + h * 512, sb + B_STAT + h * 8, lane, tag);
      STAMP(2 + h, l * 16 + 3);
      uint4* hb = g_h + half * 8 * 1536;
      mbar_wait(afree, p0);
      mbar_wait(own, p0); p0 ^= 1;
      STAMP(2 + h, l * 16 + 5);
      if (lane == 0) { bulk_s2g(hb + r * 1536, abase, 8192); bulk_commit(); }
      mbar_wait(own + 8, l);
      if (lane == 0) { bulk_s2g(hb + r * 1536 + 512, abase + 8192, 8192); bulk_commit(); }
      mbar_wait(own + 16, l);
      if (lane == 0) {
        bulk_s2g(hb + r * 1536 + 1024, abase + 16384, 6144); bulk_commit();
        bulk_wait<0>();
      }
      __syncwarp();
      if (lane < 8) st_relaxed_u32(flags + lane * 32 + r, ev + 3);
      STAMP(2 + h, l * 16 + 6);
      wait_flags(flags + r * 32 + ((r + 2 * (lane & 3)) & 7), ev + 3);
      STAMP(2 + h, l * 16 + 13);
#pragma unroll 1
      for (int b = 3; b < 12; b++) {
        const int t = b / 3, bb = b - 3 * t, j = (r + 2 * t) & 7, slot = b & 7;
        if (b == 8) mbar_wait(afree + 8, l);
        if (b == 11) mbar_wait(afree + 16, l);
        if (elect_one()) {
          const uint32_t bytes = bb == 2 ? 6144 : 8192;
          mbar_expect_tx(afull + slot * 8, bytes);
          bulk_g2s(abase + slot * 8192, hb + j * 1536 + bb * 512, bytes, afull + slot * 8);
        }
        __syncwarp();
      }
      STAMP(2 + h, l * 16 + 7);
      mbar_wait(own, p0);
      STAMP(2 + h, l * 16 + 8);
      if (l == 0) {
        publish_chunk(g_act + (2 * 32 + half) * 4096 + r * 512, abase, flags + r, ev + 6, lane);
        mbar_wait(afree, p0); p0 ^= 1;
        fetch_chunks(g_act + (2 * 32 + half) * 4096, flags, abase, afull, r, ev + 6, lane);
        STAMP(2 + h, l * 16 + 9);
        gather_stats(g_stats + (2 * 32 + half) * 512, sb + SM_STAT + h * 512, sb + B_STAT + h * 8, lane, tag);
      } else if (lane == 0) {
        tma_store(&tm_out, abase, 64 * r, 128 * cb + 64 * h); bulk_commit(); bulk_wait<0>();
      }
      STAMP(2 + h, l * 16 + 10);
    }
  } else {
    const uint32_t par = epoch & 1, tag = par ^ 1;
    colsum_task(wqkv + 64 * r + 8 * (lane & 7), 3 * kD, true, 32 * cb, g_cs + ((r * 2 + 0) * 16 + cb) * 48 + 2 * (lane & 7), lane, tag);
    for (int i = lane; i < 136; i += 32) g_kv[(((par ^ 1) * 2 + (i >= 68)) * 8 + r) * 1088 + cb * 68 + (i >= 68 ? i - 68 : i)] = 0.f;
    colsum_gather(g_cs + (r * 2 + 0) * 16 * 48, sb + SM_CS, 48, sb + B_CSRDY, lane, tag);
    STAMP(2, 48);
    if (lane == 1) prefetch_l2((const char*)wo + bid * 4096, 4096);
    if (lane == 2) prefetch_l2((const char*)w2 + bid * 11008, 11008);
    STAMP(2, 49);
    asm volatile("barrier.cluster.wait.aligned;" ::: "memory");
    const uint32_t target = (epoch + 1) * 16;
    const int g = lane >> 2, t = lane & 3;
#pragma unroll 1
    for (int l = 0; l < 2; l++) {
      mbar_wait(sb + B_KVDONE, l);
      STAMP(2, 50 + l * 4);
      if (lane == 0) { fence_gpu(); red_add_u32(g_cnt + (l * 8 + r) * 32, 1); }
      STAMP(2, 51 + l * 4);
      wait_flag_acq(g_cnt + (l * 8 + r) * 32, target);
      STAMP(2, 52 + l * 4);
      const float* kv = g_kv + ((par * 2 + l) * 8 + r) * 1088;
      float2 v[24];
#pragma unroll
      for (int hh = 0; hh < 4; hh++) {
        v[hh * 6 + 0] = ld_relaxed_f2(kv + hh * 272 + g * 16 + 2 * t);        v[hh * 6 + 1] = ld_relaxed_f2(kv + hh * 272 + g * 16 + 8 + 2 * t);
        v[hh * 6 + 2] = ld_relaxed_f2(kv + hh * 272 + (8 + g) * 16 + 2 * t);  v[hh * 6 + 3] = ld_relaxed_f2(kv + hh * 272 + (8 + g) * 16 + 8 + 2 * t);
        v[hh * 6 + 4] = ld_relaxed_f2(kv + hh * 272 + 256 + 2 * t);           v[hh * 6 + 5] = ld_relaxed_f2(kv + hh * 272 + 256 + 8 + 2 * t);
      }
#pragma unroll
      for (int i = 0; i < 12; i++) sts_u2(sb + SM_RING + 16384 + i * 256 + lane * 8, pack_bf16(v[2 * i].x, v[2 * i].y), pack_bf16(v[2 * i + 1].x, v[2 * i + 1].y));
      __syncwarp();
      if (lane == 0) mbar_arrive(sb + B_KVRDY);
      STAMP(2, 53 + l * 4);
      if (l == 0) colsum_gather(g_cs + (r * 2 + 1) * 16 * 48, sb + SM_CS + 768, 44, sb + B_CSRDY + 8, lane, tag);
    }
    if (lane == 0) g_epoch[bid * 8] = epoch + 1;
  }
  } else {
    asm volatile("setmaxnreg.inc.sync.aligned.u32 200;");
    const int lane = __shfl_sync(0xffffffff, threadIdx.x & 31, threadIdx.x & 31);
    const uint32_t epoch = ld_relaxed(g_epoch + bid * 8);
    const int wg0 = warp >> 2, lane0 = lane, half = cb * 2 + wg0, wg = wg0;
    const uint32_t sb0 = sb;
    STAMP(wg, 62);
    const uint32_t tag = (epoch + 1) & 1;
    uint32_t xr[16];
    uint32_t sph = 0;
    mbar_wait(sb0 + B_AFULL + wg0 * 64, 0);
#pragma unroll
    for (int s = 0; s < 4; s++)
      ldsm4(sb0 + wg0 * 65536 + (16 * (warp & 3) + 8 * ((lane0 >> 3) & 1) + (lane0 & 7)) * 128 + (((2 * s + (lane0 >> 4)) ^ (lane0 & 7)) << 4),
            xr[4 * s], xr[4 * s + 1], xr[4 * s + 2], xr[4 * s + 3]);
    asm volatile("barrier.cluster.wait.aligned;" ::: "memory");
    STAMP(wg, 63);

#pragma unroll 1
    for (int l = 0; l < 2; l++) {
      const uint32_t sb = opaque(sb0);
      const int lane = opaque(lane0), wg = opaque(wg0), wq = opaque(warp) & 3, g = lane >> 2, t = lane & 3;
      const uint32_t abase = sb + wg * 65536, afull = sb + B_AFULL + wg * 64, afree = sb + B_AFREE + wg * 24, own = sb + B_OWN + wg * 24;
      const uint32_t ring = sb + SM_RING;
      const uint32_t dA = desc_lo(abase, 16), dH = desc_lo(abase, 1024), dB = desc_lo(ring, 8192), dB2 = desc_lo(ring, SLOT);
      constexpr int S4 = SLOT >> 4;
      uint32_t swa[4];
#pragma unroll
      for (int s = 0; s < 4; s++) swa[s] = abase + (16 * wq + 8 * ((lane >> 3) & 1) + (lane & 7)) * 128 + (((2 * s + (lane >> 4)) ^ (lane & 7)) << 4);
      auto wait_b = [&](int st) { mbar_wait(sb + B_BFULL + (st & 3) * 8, (st >> 2) & 1); };
      auto release_b = [&](int st) { if (lane == 0) mbar_arrive(sb + B_BEMPTY + (st & 3) * 8); };
      auto signal = [&](uint32_t bar) { __syncwarp(); if (lane == 0) mbar_arrive(bar); };
      const uint32_t chk = abase + (16 * wq + g) * 128 + (((2 * t) ^ g) << 4);
      auto fetch_ok = [&](int i, uint32_t par, int buf, uint32_t tg) {
        mbar_wait(afull + i * 8, par);
        if (__builtin_expect(!__all_sync(0xffffffff, (((lds_u32(chk + i * 8192) ^ tg) | (lds_u32(chk + (i * 8192 + 1024)) ^ tg)) & 1u) == 0), 0)) {
          const uint4* src = g_act + (buf * 32 + opaque(half)) * 4096 + ((opaque(r) + i) & 7) * 512 + wq * 128 + opaque(lane);
          const uint32_t dst = abase + i * 8192 + wq * 2048 + opaque(lane) * 16;
          uint32_t cnt = 0;
          do {
#pragma unroll 1
            for (int u = 0; u < 4; u++) sts_u4(dst + u * 512, ld_relaxed_u4(src + u * 32));
            fence_async_smem();
            __syncwarp();
            if (++cnt > SPIN_LIMIT) __trap();
          } while (!__all_sync(0xffffffff, (((lds_u32(chk + i * 8192) ^ tg) | (lds_u32(chk + (i * 8192 + 1024)) ^ tg)) & 1u) == 0));
        }
      };
      const uint32_t hchk = abase + (lane >> 4) * 2048 + ((lane >> 3) & 1) * 1024 + (2 * wq + ((lane >> 2) & 1)) * 128 + (lane & 3) * 32 + g * 4;
      const uint32_t hchk3 = hchk + (lane >= 16 ? 0 : 4096);
      auto fetch_h_ok = [&](int b  , uint32_t par, uint32_t tg) {
        const int slot = b & 7, bb = b % 3;
        mbar_wait(afull + slot * 8, par);
        const uint32_t a1 = hchk + slot * 8192, a2 = bb == 2 ? hchk3 + slot * 8192 : hchk + (slot * 8192 + 4096);
        if (__builtin_expect(!__all_sync(0xffffffff, (((lds_u32(a1) ^ tg) | (lds_u32(a2) ^ tg)) >> 31) == 0), 0)) {
          const int ln = opaque(lane);
          const uint32_t off = (ln >> 4) * 1024 + wq * 256 + (ln & 15) * 16;
          const uint4* src = g_h + (opaque(half) * 8 + ((opaque(r) + 2 * (b / 3)) & 7)) * 1536 + bb * 512 + off / 16;
          uint32_t cnt = 0;
          do {
#pragma unroll 1
            for (int u = 0; u < (bb == 2 ? 3 : 4); u++) sts_u4(abase + slot * 8192 + u * 2048 + off, ld_relaxed_u4(src + u * 128));
            fence_async_smem();
            __syncwarp();
            if (++cnt > SPIN_LIMIT) __trap();
          } while (!__all_sync(0xffffffff, (((lds_u32(a1) ^ tg) | (lds_u32(a2) ^ tg)) >> 31) == 0));
        }
      };
      const uint32_t tmask = t == 0 ? 1u : 0u;
      auto store_chunk = [&](const uint32_t (&v)[16], uint32_t tg  , uint32_t msk) {
#pragma unroll
        for (int s = 0; s < 4; s++) stsm4(swa[s], (v[4 * s] & ~msk) | tg, (v[4 * s + 1] & ~msk) | tg, v[4 * s + 2], v[4 * s + 3]);
        fence_async_smem();
        signal(own);
      };
      auto stat_dst = [&](int ln) -> float2* { return g_stats + (ln * 32 + opaque(half)) * 512 + opaque(r) * 64 + 16 * wq + g; };
      const uint32_t stat_sm = sb + SM_STAT + (wg * 64 + 16 * wq + g) * 8;
      const uint32_t cs_sm = sb + SM_CS + 8 * t;
      const uint32_t ltag = l ^ 1;
      float rs0, rs1;
      {
        float ak[32], av[32], aq[32];
        STAMP(wg, l * 24 + 0);
        {
          wait_b(0);
          wg_fence();
          wgmma_n128_init<0, 0, HI_SW>(ak, av, dA, dB);
          static_for<1, 4>([&](auto K) { wgmma_n128<2 * K.value, 128 * K.value, HI_SW>(ak, av, dA, dB); });
          wg_commit();
          publish_stats(xr, stat_dst(2 * l), t, tag);
        }
        static_for<1, 8>([&](auto I) {
          constexpr int i = I.value;
          if (l == 0) mbar_wait(afull + i * 8, 0); else fetch_ok(i, i == 3, 2, tag);
          if (i == 1) STAMP(wg, l * 2 + 19);
          wait_b(i);
          wg_fence();
          static_for<0, 4>([&](auto K) { wgmma_n128<i * 512 + 2 * K.value, (i & 3) * S4 + 128 * K.value, HI_SW>(ak, av, dA, dB); });
          wg_commit();
          wg_wait<1>(); release_b(i - 1);
        });
        STAMP(wg, l * 24 + 1);
        static_for<0, 3>([&](auto I) {
          constexpr int i = I.value;
          wait_b(8 + i);
          wg_fence();
          static_for<0, 8>([&](auto K) {
            constexpr int k = K.value;
            if constexpr (i == 0 && k == 0) wgmma_n64_init<0, 0, HI_SW>(aq, dA, dB);
            else wgmma_n64<i * 1024 + (k >> 2) * 512 + 2 * (k & 3), i * S4 + 128 * k, HI_SW>(aq, dA, dB);
          });
          wg_commit();
          if (i == 0) { wg_wait<1>(); release_b(7); }
        });
        fence_regs(ak); fence_regs(av);
        if (l == 0) mbar_wait(sb + B_CSRDY, 0);
        mbar_wait(sb + B_STAT + wg * 8, sph); sph ^= 1;
        const float2 s0 = lds_f2(stat_sm), s1 = lds_f2(stat_sm + 64);
        const float y0 = s0.x * 1.4426950408889634f, y1 = s1.x * 1.4426950408889634f;
        STAMP(wg, l * 24 + 2);
        const uint32_t pk_s = ring + (2 * wg) * SLOT + 16384, v_s = ring + (2 * wg + 1) * SLOT + 16384;
        {
          float2 c[16];
#pragma unroll
          for (int j = 0; j < 16; j++) c[j] = lds_f2(cs_sm + (64 + 8 * j) * 4);
          uint32_t pk[16], pv[16];
#pragma unroll
          for (int j = 0; j < 8; j++) {
            pk[2 * j] = pack_bf16(phi_y(y0 * fmaf(s0.y, c[j].x, ak[4 * j])), phi_y(y0 * fmaf(s0.y, c[j].y, ak[4 * j + 1])));
            pk[2 * j + 1] = pack_bf16(phi_y(y1 * fmaf(s1.y, c[j].x, ak[4 * j + 2])), phi_y(y1 * fmaf(s1.y, c[j].y, ak[4 * j + 3])));
            pv[2 * j] = pack_bf16(s0.x * fmaf(s0.y, c[8 + j].x, av[4 * j]), s0.x * fmaf(s0.y, c[8 + j].y, av[4 * j + 1]));
            pv[2 * j + 1] = pack_bf16(s1.x * fmaf(s1.y, c[8 + j].x, av[4 * j + 2]), s1.x * fmaf(s1.y, c[8 + j].y, av[4 * j + 3]));
          }
#pragma unroll
          for (int s = 0; s < 4; s++) {
            stsm4(swa[s] + (pk_s - abase), pk[4 * s], pk[4 * s + 1], pk[4 * s + 2], pk[4 * s + 3]);
            stsm4(swa[s] + (pk_s - abase) + SLOT, pv[4 * s], pv[4 * s + 1], pv[4 * s + 2], pv[4 * s + 3]);
          }
        }
        wg_bar(wg);
        {
          float c0[4] = {0.f, 0.f, 0.f, 0.f}, c1[4] = {0.f, 0.f, 0.f, 0.f}, z0[4] = {0.f, 0.f, 0.f, 0.f}, z1[4] = {0.f, 0.f, 0.f, 0.f};
          const int m = lane >> 3;
#pragma unroll
          for (int ks = 0; ks < 4; ks++) {
            uint32_t a0, a1, a2, a3, b0, b1, b2, b3;
            const int ra = 16 * ks + 8 * (m >> 1) + (lane & 7), rb = 16 * ks + 8 * (m & 1) + (lane & 7);
            ldsm4t(v_s + ra * 128 + (((2 * wq + (m & 1)) ^ (lane & 7)) << 4), a0, a1, a2, a3);
            ldsm4t(pk_s + rb * 128 + (((2 * wq + (m >> 1)) ^ (lane & 7)) << 4), b0, b1, b2, b3);
            mma16816(c0, a0, a1, a2, a3, b0, b1);
            mma16816(c1, a0, a1, a2, a3, b2, b3);
            mma16816(z0, 0x3f803f80u, 0x3f803f80u, 0x3f803f80u, 0x3f803f80u, b0, b1);
            mma16816(z1, 0x3f803f80u, 0x3f803f80u, 0x3f803f80u, 0x3f803f80u, b2, b3);
          }
          float* kv = g_kv + (((epoch & 1) * 2 + l) * 8 + opaque(r)) * 1088 + wq * 272;
          red_add_f2(kv + g * 16 + 2 * t, c0[0], c0[1]); red_add_f2(kv + (g + 8) * 16 + 2 * t, c0[2], c0[3]);
          red_add_f2(kv + g * 16 + 8 + 2 * t, c1[0], c1[1]); red_add_f2(kv + (g + 8) * 16 + 8 + 2 * t, c1[2], c1[3]);
          if (g == 0) { red_add_f2(kv + 256 + 2 * t, z0[0], z0[1]); red_add_f2(kv + 256 + 8 + 2 * t, z1[0], z1[1]); }
          signal(sb + B_KVDONE);
        }
        STAMP(wg, l * 24 + 3);
        wg_wait<2>(); release_b(8);
        {
          wait_b(11);
          wg_fence();
          static_for<0, 8>([&](auto K) { wgmma_n64<3 * 1024 + (K.value >> 2) * 512 + 2 * (K.value & 3), 3 * S4 + 128 * K.value, HI_SW>(aq, dA, dB); });
          wg_commit();
        }
        float2 c[8];
#pragma unroll
        for (int j = 0; j < 8; j++) c[j] = lds_f2(cs_sm + 8 * j * 4);
        wg_wait<2>(); release_b(9);
        wg_wait<1>(); release_b(10);
        wg_wait<0>(); release_b(11);
        fence_regs(aq);
        if (lane == 0) mbar_arrive(afree);
        STAMP(wg, l * 24 + 4);
        uint32_t pq[16];
#pragma unroll
        for (int j = 0; j < 8; j++) {
          pq[2 * j] = pack_bf16(phi_y(y0 * fmaf(s0.y, c[j].x, aq[4 * j])), phi_y(y0 * fmaf(s0.y, c[j].y, aq[4 * j + 1])));
          pq[2 * j + 1] = pack_bf16(phi_y(y1 * fmaf(s1.y, c[j].x, aq[4 * j + 2])), phi_y(y1 * fmaf(s1.y, c[j].y, aq[4 * j + 3])));
        }
        STAMP(wg, l * 24 + 5);
        mbar_wait(sb + B_KVRDY, l);
        STAMP(wg, l * 24 + 6);
        uint2 f[12];
#pragma unroll
        for (int i = 0; i < 12; i++) f[i] = lds_u2(ring + 16384 + i * 256 + lane * 8);
        float cn[4][8], cz[4][4];
#pragma unroll
        for (int hh = 0; hh < 4; hh++) {
          float c0[4] = {0.f, 0.f, 0.f, 0.f}, c1[4] = {0.f, 0.f, 0.f, 0.f};
          cz[hh][0] = cz[hh][1] = cz[hh][2] = cz[hh][3] = 0.f;
          mma16816(cz[hh], pq[4 * hh], pq[4 * hh + 1], pq[4 * hh + 2], pq[4 * hh + 3], f[3 * hh + 2].x, f[3 * hh + 2].y);
          mma16816(c0, pq[4 * hh], pq[4 * hh + 1], pq[4 * hh + 2], pq[4 * hh + 3], f[3 * hh].x, f[3 * hh].y);
          mma16816(c1, pq[4 * hh], pq[4 * hh + 1], pq[4 * hh + 2], pq[4 * hh + 3], f[3 * hh + 1].x, f[3 * hh + 1].y);
#pragma unroll
          for (int u = 0; u < 4; u++) { cn[hh][u] = c0[u]; cn[hh][4 + u] = c1[u]; }
        }
        uint32_t o[16];
#pragma unroll
        for (int hh = 0; hh < 4; hh++) {
          const float i0 = rcp(cz[hh][0] + 1e-6f), i1 = rcp(cz[hh][2] + 1e-6f);
          o[4 * hh] = pack_bf16(cn[hh][0] * i0, cn[hh][1] * i0); o[4 * hh + 1] = pack_bf16(cn[hh][2] * i1, cn[hh][3] * i1);
          o[4 * hh + 2] = pack_bf16(cn[hh][4] * i0, cn[hh][5] * i0); o[4 * hh + 3] = pack_bf16(cn[hh][6] * i1, cn[hh][7] * i1);
        }
        store_chunk(o, ltag & tmask, tmask);
        wg_bar(wg);
        STAMP(wg, l * 24 + 7);
      }
      {
        float acc[32];
        {
          wait_b(12);
          wg_fence();
          wgmma_n64_init<0, 0, HI_SW>(acc, dA, dB);
          static_for<1, 4>([&](auto K) { wgmma_n64<2 * K.value, 128 * K.value, HI_SW>(acc, dA, dB); });
          wg_commit();
        }
        static_for<1, 8>([&](auto I) {
          constexpr int i = I.value;
          if ((i & 1) == 0) wait_b(12 + i / 2);
          fetch_ok(i, i == 3 ? ltag : 1u, 0, ltag);
          if (i == 1) STAMP(wg, l * 24 + 8);
          if (l == 1) STAMP(wg, 43 + i);
          wg_fence();
          static_for<0, 4>([&](auto K) { wgmma_n64<i * 512 + 2 * K.value, (i / 2) * S4 + (i & 1) * 512 + 128 * K.value, HI_SW>(acc, dA, dB); });
          wg_commit();
          if ((i & 1) == 0) { wg_wait<1>(); release_b(11 + i / 2); }
        });
        wg_wait<0>(); release_b(15);
        fence_regs(acc);
        if (lane == 0) mbar_arrive(afree);
        STAMP(wg, l * 24 + 9);
#pragma unroll
        for (int j = 0; j < 8; j++) {
          xr[2 * j] = pack_bf16(bf_lo(xr[2 * j]) + acc[4 * j], bf_hi(xr[2 * j]) + acc[4 * j + 1]);
          xr[2 * j + 1] = pack_bf16(bf_lo(xr[2 * j + 1]) + acc[4 * j + 2], bf_hi(xr[2 * j + 1]) + acc[4 * j + 3]);
        }
        store_chunk(xr, ltag & tmask, tmask);
        wg_bar(wg);
        STAMP(wg, l * 24 + 10);
      }
      {
        float acc[88];
        {
          wait_b(16);
          wg_fence();
          wgmma_n176_init<0, 0, HI_SW>(acc, dA, dB);
          static_for<1, 4>([&](auto K) { wgmma_n176<2 * K.value, 128 * K.value, HI_SW>(acc, dA, dB); });
          wg_commit();
          publish_stats(xr, stat_dst(2 * l + 1), t, tag);
        }
        static_for<1, 8>([&](auto I) {
          constexpr int i = I.value;
          fetch_ok(i, i == 3 ? (uint32_t)l : 0u, 1, ltag);
          if (i == 1) STAMP(wg, l * 24 + 11);
          wait_b(16 + i);
          wg_fence();
          static_for<0, 4>([&](auto K) { wgmma_n176<i * 512 + 2 * K.value, (i & 3) * S4 + 128 * K.value, HI_SW>(acc, dA, dB); });
          wg_commit();
          wg_wait<1>(); release_b(15 + i);
        });
        if (l == 0) mbar_wait(sb + B_CSRDY + 8, 0);
        mbar_wait(sb + B_STAT + wg * 8, sph); sph ^= 1;
        const float2 s0 = lds_f2(stat_sm), s1 = lds_f2(stat_sm + 64);
        float2 c[22];
#pragma unroll
        for (int j = 0; j < 22; j++) c[j] = lds_f2(cs_sm + (192 + 8 * j) * 4);
        const uint32_t sgn = ltag ? 0x80008000u : 0u;
        rs0 = ltag ? -s0.x : s0.x; rs1 = ltag ? -s1.x : s1.x;
        wg_wait<0>(); release_b(23);
        fence_regs(acc);
        if (lane == 0) mbar_arrive(afree);
        STAMP(wg, l * 24 + 12);
        const uint32_t hrow = abase + (lane >> 4) * 1024 + (2 * wq + ((lane >> 3) & 1)) * 128 + (lane & 7) * 16;
#pragma unroll
        for (int b = 0; b < 3; b++) {
          uint32_t p[16];
#pragma unroll
          for (int u = 0; u < (b == 2 ? 6 : 8); u++) {
            const int j = 8 * b + u;
            p[2 * u] = pack_bf16_relu(fmaf(s0.y, c[j].x, acc[4 * j]), fmaf(s0.y, c[j].y, acc[4 * j + 1])) ^ sgn;
            p[2 * u + 1] = pack_bf16_relu(fmaf(s1.y, c[j].x, acc[4 * j + 2]), fmaf(s1.y, c[j].y, acc[4 * j + 3])) ^ sgn;
          }
#pragma unroll
          for (int s = 0; s < (b == 2 ? 3 : 4); s++) stsm4(hrow + (4 * b + s) * 2048, p[4 * s], p[4 * s + 1], p[4 * s + 2], p[4 * s + 3]);
          fence_async_smem(); signal(own + b * 8);
        }
        wg_bar(wg);
        STAMP(wg, l * 24 + 13);
      }
      {
        float ap[32], ao[32];
        float bp[32], bo[32];
        const uint32_t htag = ltag << 31;
        {
          wait_b(24); wait_b(25);
          wg_fence();
          wgmma_n128_init<0, 0, HI_NS>(ap, ao, dH, dB2);
          static_for<1, 11>([&](auto K) { wgmma_n128<128 * K.value, 128 * K.value, HI_NS>(ap, ao, dH, dB2); });
          wg_commit();
        }
        static_for<1, 3>([&](auto TT) {
          constexpr int tt = TT.value;
          wait_b(24 + 2 * tt); wait_b(25 + 2 * tt);
          static_for<0, 3>([&](auto BB) {
            constexpr int bb = BB.value, slot = (3 * tt + bb) & 7;
            fetch_h_ok(3 * tt + bb, (slot == 3 || slot == 0) ? ltag : 1u, htag);
            if (tt == 1 && bb == 0) STAMP(wg, l * 24 + 14);
            if (l == 1) STAMP(wg, 48 + 3 * tt + bb);
            wg_fence();
            static_for<0, (bb == 2 ? 3 : 4)>([&](auto K) { wgmma_n128<slot * 512 + 128 * K.value, ((2 * tt) & 3) * S4 + 128 * (4 * bb + K.value), HI_NS>(ap, ao, dH, dB2); });
            wg_commit();
            if (bb == 0) {
              wg_wait<1>(); release_b(22 + 2 * tt); release_b(23 + 2 * tt);
              if (lane == 0) mbar_arrive(afree + 8 * tt);
              if (tt == 2 && lane == 0) { mbar_arrive_remote(mapa(sb + B_PFREE + wg * 8, (r & 1) ^ 1)); if (wq == 0) mbar_expect_tx(sb + B_PRDY + wg * 8, 8192); }
            }
          });
        });
        {
          wait_b(30);
          static_for<0, 3>([&](auto BB) {
            constexpr int bb = BB.value;
            fetch_h_ok(9 + bb, bb == 2 ? (uint32_t)l : 1u, htag);
            if (l == 1) STAMP(wg, 57 + bb);
            wg_fence();
            static_for<0, (bb == 2 ? 3 : 4)>([&](auto K) {
              if constexpr (bb == 0 && K.value == 0) wgmma_n64_init<512, 2 * S4, HI_NS>(bp, dH, dB2);
              else wgmma_n64<(1 + bb) * 512 + 128 * K.value, 2 * S4 + 128 * (4 * bb + K.value), HI_NS>(bp, dH, dB2);
            });
            wg_commit();
            if (bb == 0) { wg_wait<1>(); release_b(28); release_b(29); }
          });
          wait_b(31);
          wg_fence();
          wgmma_n64_init<512, 3 * S4, HI_NS>(bo, dH, dB2);
          static_for<1, 11>([&](auto K) { wgmma_n64<512 + 128 * K.value, 3 * S4 + 128 * K.value, HI_NS>(bo, dH, dB2); });
          wg_commit();
          wg_wait<1>(); release_b(30);
          fence_regs(ap); fence_regs(ao); fence_regs(bp);
          STAMP(wg, l * 24 + 15);
          mbar_wait(sb + B_PFREE + wg * 8, l);
          const uint32_t rdst = mapa(abase + 4 * 8192 + (wq * 32 + lane) * 16, (r & 1) ^ 1), rbar = mapa(sb + B_PRDY + wg * 8, (r & 1) ^ 1);
#pragma unroll
          for (int i = 0; i < 4; i++)
            st_async_v4(rdst + i * 2048, pack_bf16(ap[8 * i] + bp[8 * i], ap[8 * i + 1] + bp[8 * i + 1]), pack_bf16(ap[8 * i + 2] + bp[8 * i + 2], ap[8 * i + 3] + bp[8 * i + 3]),
                        pack_bf16(ap[8 * i + 4] + bp[8 * i + 4], ap[8 * i + 5] + bp[8 * i + 5]), pack_bf16(ap[8 * i + 6] + bp[8 * i + 6], ap[8 * i + 7] + bp[8 * i + 7]), rbar);
          wg_wait<0>(); release_b(31);
          fence_regs(bo);
#pragma unroll
          for (int i = 0; i < 32; i++) ao[i] += bo[i];
          STAMP(wg, l * 24 + 16);
          mbar_wait(sb + B_PRDY + wg * 8, l);
          STAMP(wg, l * 24 + 17);
          uint4 p[4];
#pragma unroll
          for (int i = 0; i < 4; i++) p[i] = lds_u4(abase + 4 * 8192 + i * 2048 + (wq * 32 + lane) * 16);
#pragma unroll
          for (int i = 0; i < 4; i++) {
            xr[4 * i] = pack_bf16(fmaf(rs0, ao[8 * i] + bf_lo(p[i].x), bf_lo(xr[4 * i])), fmaf(rs0, ao[8 * i + 1] + bf_hi(p[i].x), bf_hi(xr[4 * i])));
            xr[4 * i + 1] = pack_bf16(fmaf(rs1, ao[8 * i + 2] + bf_lo(p[i].y), bf_lo(xr[4 * i + 1])), fmaf(rs1, ao[8 * i + 3] + bf_hi(p[i].y), bf_hi(xr[4 * i + 1])));
            xr[4 * i + 2] = pack_bf16(fmaf(rs0, ao[8 * i + 4] + bf_lo(p[i].z), bf_lo(xr[4 * i + 2])), fmaf(rs0, ao[8 * i + 5] + bf_hi(p[i].z), bf_hi(xr[4 * i + 2])));
            xr[4 * i + 3] = pack_bf16(fmaf(rs1, ao[8 * i + 6] + bf_lo(p[i].w), bf_lo(xr[4 * i + 3])), fmaf(rs1, ao[8 * i + 7] + bf_hi(p[i].w), bf_hi(xr[4 * i + 3])));
          }
          signal(afree);
          store_chunk(xr, l == 0 ? (tag & tmask) : 0u, l == 0 ? tmask : 0u);
          wg_bar(wg);
          STAMP(wg, l * 24 + 18);
        }
      }
      if (l == 0) asm volatile("" ::: "memory");
    }

  }
}

typedef CUresult (*EncodeFn)(CUtensorMap*, CUtensorMapDataType, cuuint32_t, void*, const cuuint64_t*, const cuuint64_t*, const cuuint32_t*,
                             const cuuint32_t*, CUtensorMapInterleave, CUtensorMapSwizzle, CUtensorMapL2promotion, CUtensorMapFloatOOBfill);

CUtensorMap make_map(EncodeFn enc, const void* ptr, uint64_t cols, uint64_t rows, uint32_t box_rows) {
  CUtensorMap m;
  cuuint64_t gd[2] = {cols, rows}, gs[1] = {cols * 2};
  cuuint32_t bd[2] = {64, box_rows}, es[2] = {1, 1};
  enc(&m, CU_TENSOR_MAP_DATA_TYPE_BFLOAT16, 2, const_cast<void*>(ptr), gd, gs, bd, es, CU_TENSOR_MAP_INTERLEAVE_NONE,
      CU_TENSOR_MAP_SWIZZLE_128B, CU_TENSOR_MAP_L2_PROMOTION_L2_128B, CU_TENSOR_MAP_FLOAT_OOB_FILL_NONE);
  return m;
}

}

extern "C" void kernel_launch(void* const* d_in, const int* in_sizes, int n_in, void* d_out, int out_size) {
  (void)in_sizes; (void)n_in; (void)out_size;
  const __nv_bfloat16* x = (const __nv_bfloat16*)d_in[0];
  const __nv_bfloat16* wqkv = (const __nv_bfloat16*)d_in[1];
  const __nv_bfloat16* wo = (const __nv_bfloat16*)d_in[2];
  const __nv_bfloat16* w1 = (const __nv_bfloat16*)d_in[4];
  const __nv_bfloat16* w2 = (const __nv_bfloat16*)d_in[5];
  void* fn = nullptr;
  cudaDriverEntryPointQueryResult q;
  cudaGetDriverEntryPoint("cuTensorMapEncodeTiled", &fn, cudaEnableDefault, &q);
  EncodeFn enc = (EncodeFn)fn;
  const CUtensorMap tm_x = make_map(enc, x, kD, kS, 64), tm_out = make_map(enc, d_out, kD, kS, 64),
                    tm_wqkv = make_map(enc, wqkv, 3 * kD, kD, 64), tm_wo = make_map(enc, wo, kD, kD, 64),
                    tm_w1 = make_map(enc, w1, kFF, kD, 64), tm_w2 = make_map(enc, w2, kD, kFF, kHS);
  cudaFuncSetAttribute(fused_kernel, cudaFuncAttributeMaxDynamicSharedMemorySize, SM_TOTAL);
  fused_kernel<<<128, 384, SM_TOTAL>>>(tm_x, tm_out, tm_wqkv, tm_wo, tm_w1, tm_w2, wqkv, wo, w1, w2);
}
```

```cpp
#include <cuda_runtime.h>
#include <cuda_bf16.h>
#include <cuda.h>
#include <stdint.h>

#define NOCHECK 0
#define NOFENCE 0
#define PRIO 0
#define MAPPING 0
namespace {

constexpr int kS = 2048, kD = 512, kFF = 1376, kHS = 176;
constexpr uint32_t SM_RING = 131072, SLOT = 24576, SM_MISC = 229376;
constexpr uint32_t SM_STAT = SM_MISC;
constexpr uint32_t SM_CS = SM_MISC + 1024;
constexpr uint32_t SM_BAR = SM_CS + 1472;
constexpr uint32_t B_BFULL = SM_BAR, B_BEMPTY = SM_BAR + 32, B_AFULL = SM_BAR + 64  ,
                   B_AFREE = SM_BAR + 192  , B_OWN = SM_BAR + 240  , B_STAT = SM_BAR + 288  ,
                   B_CSRDY = SM_BAR + 304  , B_KVDONE = SM_BAR + 320, B_KVRDY = SM_BAR + 328,
                   B_PRDY = SM_BAR + 336  , B_PFREE = SM_BAR + 352  ;
constexpr uint32_t SM_TOTAL = SM_BAR + 368;
static_assert(SM_TOTAL <= 232448, "smem");
constexpr uint32_t SPIN_LIMIT = 1u << 22;

__device__ uint32_t g_epoch[128 * 8];
__device__ __align__(128) uint4 g_flags[32 * 8 * 8 * 2];
__device__ __align__(16) float4 g_cs[8 * 2 * 16 * 48];
__device__ __align__(128) float4 g_kv[2 * 8 * 384];
__device__ __align__(128) float2 g_stats[4 * 32 * 64 * 8];
__device__ __align__(1024) uint4 g_act[3 * 32 * 8 * 512];
__device__ __align__(1024) uint4 g_h[32 * 8 * 3 * 512];
#define STAMP(role, i) do {} while (0)

__device__ __forceinline__ uint32_t smem_u32(const void* p) { return (uint32_t)__cvta_generic_to_shared(p); }
__device__ __forceinline__ void mbar_init(uint32_t bar, uint32_t cnt) { asm volatile("mbarrier.init.shared::cta.b64 [%0], %1;" :: "r"(bar), "r"(cnt)); }
__device__ __forceinline__ void mbar_expect_tx(uint32_t bar, uint32_t bytes) { asm volatile("mbarrier.arrive.expect_tx.shared::cta.b64 _, [%0], %1;" :: "r"(bar), "r"(bytes) : "memory"); }
__device__ __forceinline__ void mbar_arrive(uint32_t bar) { asm volatile("mbarrier.arrive.shared::cta.b64 _, [%0];" :: "r"(bar) : "memory"); }
__device__ __forceinline__ void mbar_arrive_remote(uint32_t bar) { asm volatile("mbarrier.arrive.shared::cluster.b64 _, [%0];" :: "r"(bar) : "memory"); }
__device__ __forceinline__ void mbar_wait(uint32_t bar, uint32_t parity) {
  asm volatile("{\n.reg .pred p;\n.reg .u32 c;\nmov.u32 c, 0;\nWAIT_LOOP:\n"
               "mbarrier.try_wait.parity.shared::cta.b64 p, [%0], %1;\n@p bra WAIT_DONE;\n"
               "add.u32 c, c, 1;\nsetp.lt.u32 p, c, %2;\n@p bra WAIT_LOOP;\ntrap;\nWAIT_DONE:\n}"
               :: "r"(bar), "r"(parity), "n"(SPIN_LIMIT) : "memory");
}
__device__ __forceinline__ uint32_t mapa(uint32_t addr, uint32_t rank) { uint32_t r; asm volatile("mapa.shared::cluster.u32 %0, %1, %2;" : "=r"(r) : "r"(addr), "r"(rank)); return r; }
__device__ __forceinline__ bool elect_one() { uint32_t p; asm volatile("{\n.reg .pred P;\nelect.sync _|P, 0xffffffff;\nselp.u32 %0, 1, 0, P;\n}" : "=r"(p)); return p; }
__device__ __forceinline__ void bulk_g2s(uint32_t dst, const void* src, uint32_t bytes, uint32_t bar) {
  asm volatile("cp.async.bulk.shared::cluster.global.mbarrier::complete_tx::bytes [%0], [%1], %2, [%3];" :: "r"(dst), "l"(src), "r"(bytes), "r"(bar) : "memory");
}
__device__ __forceinline__ void bulk_s2g(void* dst, uint32_t src, uint32_t bytes) { asm volatile("cp.async.bulk.global.shared::cta.bulk_group [%0], [%1], %2;" :: "l"(dst), "r"(src), "r"(bytes) : "memory"); }
__device__ __forceinline__ void bulk_commit() { asm volatile("cp.async.bulk.commit_group;" ::: "memory"); }
template <int N> __device__ __forceinline__ void bulk_wait() { asm volatile("cp.async.bulk.wait_group %0;" :: "n"(N) : "memory"); }
__device__ __forceinline__ void tma_load(uint32_t dst, const CUtensorMap* m, int c0, int c1, uint32_t bar) {
  asm volatile("cp.async.bulk.tensor.2d.shared::cluster.global.mbarrier::complete_tx::bytes [%0], [%1, {%3, %4}], [%2];" :: "r"(dst), "l"(m), "r"(bar), "r"(c0), "r"(c1) : "memory");
}
__device__ __forceinline__ void tma_store(const CUtensorMap* m, uint32_t src, int c0, int c1) {
  asm volatile("cp.async.bulk.tensor.2d.global.shared::cta.bulk_group [%0, {%2, %3}], [%1];" :: "l"(m), "r"(src), "r"(c0), "r"(c1) : "memory");
}
__device__ __forceinline__ void prefetch_l2(const void* p, uint32_t bytes) { asm volatile("cp.async.bulk.prefetch.L2.global [%0], %1;" :: "l"(p), "r"(bytes) : "memory"); }
__device__ __forceinline__ void prefetch_map(const CUtensorMap* m) { asm volatile("prefetch.tensormap [%0];" :: "l"(m) : "memory"); }
__device__ __forceinline__ void fence_async_smem() { asm volatile("fence.proxy.async.shared::cta;" ::: "memory"); }
__device__ __forceinline__ void fence_async_global() { asm volatile("fence.proxy.async.global;" ::: "memory"); }
__device__ __forceinline__ void fence_gpu() { asm volatile("fence.acq_rel.gpu;" ::: "memory"); }
__device__ __forceinline__ void st_release(uint32_t* p, uint32_t v) { asm volatile("st.release.gpu.global.u32 [%0], %1;" :: "l"(p), "r"(v) : "memory"); }
__device__ __forceinline__ uint32_t ld_acquire(const uint32_t* p) { uint32_t v; asm volatile("ld.acquire.gpu.global.u32 %0, [%1];" : "=r"(v) : "l"(p) : "memory"); return v; }
__device__ __forceinline__ uint32_t ld_relaxed(const uint32_t* p) { uint32_t v; asm volatile("ld.relaxed.gpu.global.u32 %0, [%1];" : "=r"(v) : "l"(p) : "memory"); return v; }
__device__ __forceinline__ float2 ld_relaxed_f2(const void* p) { float2 v; asm volatile("ld.relaxed.gpu.global.v2.f32 {%0,%1}, [%2];" : "=f"(v.x), "=f"(v.y) : "l"(p) : "memory"); return v; }
__device__ __forceinline__ float4 ld_relaxed_f4(const void* p) { float4 v; asm volatile("ld.relaxed.gpu.global.v4.f32 {%0,%1,%2,%3}, [%4];" : "=f"(v.x), "=f"(v.y), "=f"(v.z), "=f"(v.w) : "l"(p) : "memory"); return v; }
__device__ __forceinline__ void st_relaxed_b64(void* p, float a, uint32_t b) {
  asm volatile("{\n.reg .b64 v;\nmov.b64 v, {%1, %2};\nst.relaxed.gpu.global.b64 [%0], v;\n}" :: "l"(p), "r"(__float_as_uint(a)), "r"(b) : "memory");
}
__device__ __forceinline__ void red_add_u32(uint32_t* p, uint32_t v) { asm volatile("red.relaxed.gpu.global.add.u32 [%0], %1;" :: "l"(p), "r"(v) : "memory"); }
__device__ __forceinline__ void red_add_f2(float* p, float a, float b) { asm volatile("red.relaxed.gpu.global.add.v2.f32 [%0], {%1, %2};" :: "l"(p), "f"(a), "f"(b) : "memory"); }
__device__ __forceinline__ void red_add_f4(float* p, float a, float b, float c, float d) { asm volatile("red.relaxed.gpu.global.add.v4.f32 [%0], {%1, %2, %3, %4};" :: "l"(p), "f"(a), "f"(b), "f"(c), "f"(d) : "memory"); }
__device__ __forceinline__ void st_async_v4(uint32_t dst, uint32_t a, uint32_t b, uint32_t c, uint32_t d, uint32_t bar) {
  asm volatile("st.async.weak.shared::cluster.mbarrier::complete_tx::bytes.v4.b32 [%0], {%1,%2,%3,%4}, [%5];" :: "r"(dst), "r"(a), "r"(b), "r"(c), "r"(d), "r"(bar) : "memory");
}
__device__ __forceinline__ void stsm4(uint32_t addr, uint32_t a, uint32_t b, uint32_t c, uint32_t d) {
  asm volatile("stmatrix.sync.aligned.m8n8.x4.shared.b16 [%0], {%1,%2,%3,%4};" :: "r"(addr), "r"(a), "r"(b), "r"(c), "r"(d) : "memory");
}
__device__ __forceinline__ void ldsm4(uint32_t addr, uint32_t& a, uint32_t& b, uint32_t& c, uint32_t& d) {
  asm volatile("ldmatrix.sync.aligned.m8n8.x4.shared.b16 {%0,%1,%2,%3}, [%4];" : "=r"(a), "=r"(b), "=r"(c), "=r"(d) : "r"(addr) : "memory");
}
__device__ __forceinline__ void ldsm4t(uint32_t addr, uint32_t& a, uint32_t& b, uint32_t& c, uint32_t& d) {
  asm volatile("ldmatrix.sync.aligned.m8n8.x4.trans.shared.b16 {%0,%1,%2,%3}, [%4];" : "=r"(a), "=r"(b), "=r"(c), "=r"(d) : "r"(addr) : "memory");
}
__device__ __forceinline__ float2 lds_f2(uint32_t addr) { float2 v; asm volatile("ld.shared.v2.f32 {%0,%1}, [%2];" : "=f"(v.x), "=f"(v.y) : "r"(addr) : "memory"); return v; }
__device__ __forceinline__ uint32_t lds_u32(uint32_t addr) { uint32_t v; asm volatile("ld.shared.u32 %0, [%1];" : "=r"(v) : "r"(addr) : "memory"); return v; }
__device__ __forceinline__ void sts_u4(uint32_t addr, uint4 v) { asm volatile("st.shared.v4.u32 [%0], {%1,%2,%3,%4};" :: "r"(addr), "r"(v.x), "r"(v.y), "r"(v.z), "r"(v.w) : "memory"); }
__device__ __forceinline__ uint4 ld_relaxed_u4(const void* p) { uint4 v; asm volatile("ld.relaxed.gpu.global.v4.u32 {%0,%1,%2,%3}, [%4];" : "=r"(v.x), "=r"(v.y), "=r"(v.z), "=r"(v.w) : "l"(p) : "memory"); return v; }
__device__ __forceinline__ void st_relaxed_u32(uint32_t* p, uint32_t v) { asm volatile("st.relaxed.gpu.global.u32 [%0], %1;" :: "l"(p), "r"(v) : "memory"); }
__device__ __forceinline__ void st_relaxed_f4(void* p, float a, float b, float c, uint32_t d) { asm volatile("st.relaxed.gpu.global.v4.b32 [%0], {%1,%2,%3,%4};" :: "l"(p), "r"(__float_as_uint(a)), "r"(__float_as_uint(b)), "r"(__float_as_uint(c)), "r"(d) : "memory"); }
__device__ __forceinline__ uint2 lds_u2(uint32_t addr) { uint2 v; asm volatile("ld.shared.v2.u32 {%0,%1}, [%2];" : "=r"(v.x), "=r"(v.y) : "r"(addr) : "memory"); return v; }
__device__ __forceinline__ uint4 lds_u4(uint32_t addr) { uint4 v; asm volatile("ld.shared.v4.u32 {%0,%1,%2,%3}, [%4];" : "=r"(v.x), "=r"(v.y), "=r"(v.z), "=r"(v.w) : "r"(addr) : "memory"); return v; }
__device__ __forceinline__ void sts_f2(uint32_t addr, float a, float b) { asm volatile("st.shared.v2.f32 [%0], {%1,%2};" :: "r"(addr), "f"(a), "f"(b) : "memory"); }
__device__ __forceinline__ void sts_u2(uint32_t addr, uint32_t a, uint32_t b) { asm volatile("st.shared.v2.u32 [%0], {%1,%2};" :: "r"(addr), "r"(a), "r"(b) : "memory"); }
__device__ __forceinline__ void sts_f4(uint32_t addr, float4 v) { asm volatile("st.shared.v4.f32 [%0], {%1,%2,%3,%4};" :: "r"(addr), "f"(v.x), "f"(v.y), "f"(v.z), "f"(v.w) : "memory"); }
__device__ __forceinline__ void mma16816(float (&c)[4], uint32_t a0, uint32_t a1, uint32_t a2, uint32_t a3, uint32_t b0, uint32_t b1) {
  asm volatile("mma.sync.aligned.m16n8k16.row.col.f32.bf16.bf16.f32 {%0,%1,%2,%3}, {%4,%5,%6,%7}, {%8,%9}, {%0,%1,%2,%3};"
               : "+f"(c[0]), "+f"(c[1]), "+f"(c[2]), "+f"(c[3]) : "r"(a0), "r"(a1), "r"(a2), "r"(a3), "r"(b0), "r"(b1));
}
__device__ __forceinline__ uint32_t pack_bf16(float lo, float hi) { uint32_t r; asm("cvt.rn.bf16x2.f32 %0, %1, %2;" : "=r"(r) : "f"(hi), "f"(lo)); return r; }
__device__ __forceinline__ uint32_t pack_bf16_relu(float lo, float hi) { uint32_t r; asm("cvt.rn.relu.bf16x2.f32 %0, %1, %2;" : "=r"(r) : "f"(hi), "f"(lo)); return r; }
__device__ __forceinline__ float bf_lo(uint32_t v) { return __uint_as_float(v << 16); }
__device__ __forceinline__ float bf_hi(uint32_t v) { return __uint_as_float(v & 0xffff0000u); }
__device__ __forceinline__ float ex2(float x) { float y; asm("ex2.approx.ftz.f32 %0, %1;" : "=f"(y) : "f"(x)); return y; }
__device__ __forceinline__ float rcp(float x) { float y; asm("rcp.approx.ftz.f32 %0, %1;" : "=f"(y) : "f"(x)); return y; }
__device__ __forceinline__ float phi_y(float y) { return fmaf(fmaxf(y, 1.4426950408889634e-6f), 0.6931471805599453f, ex2(fminf(y, 0.f))); }
__device__ __forceinline__ int opaque(int x) { int y; asm volatile("mov.u32 %0, %1;" : "=r"(y) : "r"(x)); return y; }
__device__ __forceinline__ void wg_fence() { asm volatile("wgmma.fence.sync.aligned;" ::: "memory"); }
__device__ __forceinline__ void wg_fence_in() { if (!NOFENCE) wg_fence(); }
__device__ __forceinline__ void wg_commit() { asm volatile("wgmma.commit_group.sync.aligned;" ::: "memory"); }
template <int N> __device__ __forceinline__ void wg_wait() { asm volatile("wgmma.wait_group.sync.aligned %0;" :: "n"(N) : "memory"); }
template <int N> __device__ __forceinline__ void fence_regs(float (&d)[N]) {
#pragma unroll
  for (int i = 0; i < N; i++) asm volatile("" : "+f"(d[i]) :: "memory");
}
template <int N> __device__ __forceinline__ void zero_regs(float (&d)[N]) {
#pragma unroll
  for (int i = 0; i < N; i++) d[i] = 0.f;
  fence_regs(d);
}
__device__ __forceinline__ void wg_bar(int wg) { if (wg == 0) asm volatile("bar.sync 1, 128;" ::: "memory"); else asm volatile("bar.sync 2, 128;" ::: "memory"); }
__device__ __forceinline__ uint32_t desc_lo(uint32_t addr, uint32_t lbo) { return ((addr & 0x3FFFF) >> 4) | ((lbo >> 4) << 16); }
constexpr uint32_t HI_SW = 0x40000040u;
constexpr uint32_t HI_NS = 0x00000008u;
template <int I> struct IC { static constexpr int value = I; };
template <int B, int E, class F> __device__ __forceinline__ void static_for(F&& f) {
  if constexpr (B < E) { f(IC<B>{}); static_for<B + 1, E>(f); }
}

template <int OA, int OB, uint32_t HA>
__device__ __forceinline__ void wgmma_n64_init(float (&d)[32], uint32_t la, uint32_t lb) {
  asm volatile("{\n.reg .pred p;\n.reg .b32 ta, tb;\n.reg .b64 da, db;\n"
    "setp.ne.b32 p, 0, 0;\nadd.u32 ta, %32, %34;\nadd.u32 tb, %33, %35;\n"
    "mov.b64 da, {ta, %36};\nmov.b64 db, {tb, 0x40000040};\n"
    "wgmma.mma_async.sync.aligned.m64n64k16.f32.bf16.bf16 "
    "{%0, %1, %2, %3, %4, %5, %6, %7, %8, %9, %10, %11, %12, %13, %14, %15, "
    "%16, %17, %18, %19, %20, %21, %22, %23, %24, %25, %26, %27, %28, %29, %30, %31}, "
    "da, db, p, 1, 1, 0, 1;\n}"
    : "=f"(d[0]), "=f"(d[1]), "=f"(d[2]), "=f"(d[3]), "=f"(d[4]), "=f"(d[5]), "=f"(d[6]), "=f"(d[7]),
      "=f"(d[8]), "=f"(d[9]), "=f"(d[10]), "=f"(d[11]), "=f"(d[12]), "=f"(d[13]), "=f"(d[14]), "=f"(d[15]),
      "=f"(d[16]), "=f"(d[17]), "=f"(d[18]), "=f"(d[19]), "=f"(d[20]), "=f"(d[21]), "=f"(d[22]), "=f"(d[23]),
      "=f"(d[24]), "=f"(d[25]), "=f"(d[26]), "=f"(d[27]), "=f"(d[28]), "=f"(d[29]), "=f"(d[30]), "=f"(d[31])
    : "r"(la), "r"(lb), "n"(OA), "n"(OB), "n"(HA));
}
template <int OA, int OB, uint32_t HA>
__device__ __forceinline__ void wgmma_n128_init(float (&d)[32], float (&e)[32], uint32_t la, uint32_t lb) {
  asm volatile("{\n.reg .pred p;\n.reg .b32 ta, tb;\n.reg .b64 da, db;\n"
    "setp.ne.b32 p, 0, 0;\nadd.u32 ta, %64, %66;\nadd.u32 tb, %65, %67;\n"
    "mov.b64 da, {ta, %68};\nmov.b64 db, {tb, 0x40000040};\n"
    "wgmma.mma_async.sync.aligned.m64n128k16.f32.bf16.bf16 "
    "{%0, %1, %2, %3, %4, %5, %6, %7, %8, %9, %10, %11, %12, %13, %14, %15, "
    "%16, %17, %18, %19, %20, %21, %22, %23, %24, %25, %26, %27, %28, %29, %30, %31, "
    "%32, %33, %34, %35, %36, %37, %38, %39, %40, %41, %42, %43, %44, %45, %46, %47, "
    "%48, %49, %50, %51, %52, %53, %54, %55, %56, %57, %58, %59, %60, %61, %62, %63}, "
    "da, db, p, 1, 1, 0, 1;\n}"
    : "=f"(d[0]), "=f"(d[1]), "=f"(d[2]), "=f"(d[3]), "=f"(d[4]), "=f"(d[5]), "=f"(d[6]), "=f"(d[7]),
      "=f"(d[8]), "=f"(d[9]), "=f"(d[10]), "=f"(d[11]), "=f"(d[12]), "=f"(d[13]), "=f"(d[14]), "=f"(d[15]),
      "=f"(d[16]), "=f"(d[17]), "=f"(d[18]), "=f"(d[19]), "=f"(d[20]), "=f"(d[21]), "=f"(d[22]), "=f"(d[23]),
      "=f"(d[24]), "=f"(d[25]), "=f"(d[26]), "=f"(d[27]), "=f"(d[28]), "=f"(d[29]), "=f"(d[30]), "=f"(d[31]),
      "=f"(e[0]), "=f"(e[1]), "=f"(e[2]), "=f"(e[3]), "=f"(e[4]), "=f"(e[5]), "=f"(e[6]), "=f"(e[7]),
      "=f"(e[8]), "=f"(e[9]), "=f"(e[10]), "=f"(e[11]), "=f"(e[12]), "=f"(e[13]), "=f"(e[14]), "=f"(e[15]),
      "=f"(e[16]), "=f"(e[17]), "=f"(e[18]), "=f"(e[19]), "=f"(e[20]), "=f"(e[21]), "=f"(e[22]), "=f"(e[23]),
      "=f"(e[24]), "=f"(e[25]), "=f"(e[26]), "=f"(e[27]), "=f"(e[28]), "=f"(e[29]), "=f"(e[30]), "=f"(e[31])
    : "r"(la), "r"(lb), "n"(OA), "n"(OB), "n"(HA));
}
template <int OA, int OB, uint32_t HA>
__device__ __forceinline__ void wgmma_n176_init(float (&d)[88], uint32_t la, uint32_t lb) {
  asm volatile("{\n.reg .pred p;\n.reg .b32 ta, tb;\n.reg .b64 da, db;\n"
    "setp.ne.b32 p, 0, 0;\nadd.u32 ta, %88, %90;\nadd.u32 tb, %89, %91;\n"
    "mov.b64 da, {ta, %92};\nmov.b64 db, {tb, 0x40000040};\n"
    "wgmma.mma_async.sync.aligned.m64n176k16.f32.bf16.bf16 "
    "{%0, %1, %2, %3, %4, %5, %6, %7, %8, %9, %10, %11, %12, %13, %14, %15, "
    "%16, %17, %18, %19, %20, %21, %22, %23, %24, %25, %26, %27, %28, %29, %30, %31, "
    "%32, %33, %34, %35, %36, %37, %38, %39, %40, %41, %42, %43, %44, %45, %46, %47, "
    "%48, %49, %50, %51, %52, %53, %54, %55, %56, %57, %58, %59, %60, %61, %62, %63, "
    "%64, %65, %66, %67, %68, %69, %70, %71, %72, %73, %74, %75, %76, %77, %78, %79, "
    "%80, %81, %82, %83, %84, %85, %86, %87}, "
    "da, db, p, 1, 1, 0, 1;\n}"
    : "=f"(d[0]), "=f"(d[1]), "=f"(d[2]), "=f"(d[3]), "=f"(d[4]), "=f"(d[5]), "=f"(d[6]), "=f"(d[7]),
      "=f"(d[8]), "=f"(d[9]), "=f"(d[10]), "=f"(d[11]), "=f"(d[12]), "=f"(d[13]), "=f"(d[14]), "=f"(d[15]),
      "=f"(d[16]), "=f"(d[17]), "=f"(d[18]), "=f"(d[19]), "=f"(d[20]), "=f"(d[21]), "=f"(d[22]), "=f"(d[23]),
      "=f"(d[24]), "=f"(d[25]), "=f"(d[26]), "=f"(d[27]), "=f"(d[28]), "=f"(d[29]), "=f"(d[30]), "=f"(d[31]),
      "=f"(d[32]), "=f"(d[33]), "=f"(d[34]), "=f"(d[35]), "=f"(d[36]), "=f"(d[37]), "=f"(d[38]), "=f"(d[39]),
      "=f"(d[40]), "=f"(d[41]), "=f"(d[42]), "=f"(d[43]), "=f"(d[44]), "=f"(d[45]), "=f"(d[46]), "=f"(d[47]),
      "=f"(d[48]), "=f"(d[49]), "=f"(d[50]), "=f"(d[51]), "=f"(d[52]), "=f"(d[53]), "=f"(d[54]), "=f"(d[55]),
      "=f"(d[56]), "=f"(d[57]), "=f"(d[58]), "=f"(d[59]), "=f"(d[60]), "=f"(d[61]), "=f"(d[62]), "=f"(d[63]),
      "=f"(d[64]), "=f"(d[65]), "=f"(d[66]), "=f"(d[67]), "=f"(d[68]), "=f"(d[69]), "=f"(d[70]), "=f"(d[71]),
      "=f"(d[72]), "=f"(d[73]), "=f"(d[74]), "=f"(d[75]), "=f"(d[76]), "=f"(d[77]), "=f"(d[78]), "=f"(d[79]),
      "=f"(d[80]), "=f"(d[81]), "=f"(d[82]), "=f"(d[83]), "=f"(d[84]), "=f"(d[85]), "=f"(d[86]), "=f"(d[87])
    : "r"(la), "r"(lb), "n"(OA), "n"(OB), "n"(HA));
}
template <int OA, int OB, uint32_t HA>
__device__ __forceinline__ void wgmma_n64(float (&d)[32], uint32_t la, uint32_t lb) {
  asm volatile("{\n.reg .pred p;\n.reg .b32 ta, tb;\n.reg .b64 da, db;\n"
    "setp.eq.b32 p, 0, 0;\nadd.u32 ta, %32, %34;\nadd.u32 tb, %33, %35;\n"
    "mov.b64 da, {ta, %36};\nmov.b64 db, {tb, 0x40000040};\n"
    "wgmma.mma_async.sync.aligned.m64n64k16.f32.bf16.bf16 "
    "{%0, %1, %2, %3, %4, %5, %6, %7, %8, %9, %10, %11, %12, %13, %14, %15, "
    "%16, %17, %18, %19, %20, %21, %22, %23, %24, %25, %26, %27, %28, %29, %30, %31}, "
    "da, db, p, 1, 1, 0, 1;\n}"
    : "+f"(d[0]), "+f"(d[1]), "+f"(d[2]), "+f"(d[3]), "+f"(d[4]), "+f"(d[5]), "+f"(d[6]), "+f"(d[7]),
      "+f"(d[8]), "+f"(d[9]), "+f"(d[10]), "+f"(d[11]), "+f"(d[12]), "+f"(d[13]), "+f"(d[14]), "+f"(d[15]),
      "+f"(d[16]), "+f"(d[17]), "+f"(d[18]), "+f"(d[19]), "+f"(d[20]), "+f"(d[21]), "+f"(d[22]), "+f"(d[23]),
      "+f"(d[24]), "+f"(d[25]), "+f"(d[26]), "+f"(d[27]), "+f"(d[28]), "+f"(d[29]), "+f"(d[30]), "+f"(d[31])
    : "r"(la), "r"(lb), "n"(OA), "n"(OB), "n"(HA));
}
template <int OA, int OB, uint32_t HA>
__device__ __forceinline__ void wgmma_n128(float (&d)[32], float (&e)[32], uint32_t la, uint32_t lb) {
  asm volatile("{\n.reg .pred p;\n.reg .b32 ta, tb;\n.reg .b64 da, db;\n"
    "setp.eq.b32 p, 0, 0;\nadd.u32 ta, %64, %66;\nadd.u32 tb, %65, %67;\n"
    "mov.b64 da, {ta, %68};\nmov.b64 db, {tb, 0x40000040};\n"
    "wgmma.mma_async.sync.aligned.m64n128k16.f32.bf16.bf16 "
    "{%0, %1, %2, %3, %4, %5, %6, %7, %8, %9, %10, %11, %12, %13, %14, %15, "
    "%16, %17, %18, %19, %20, %21, %22, %23, %24, %25, %26, %27, %28, %29, %30, %31, "
    "%32, %33, %34, %35, %36, %37, %38, %39, %40, %41, %42, %43, %44, %45, %46, %47, "
    "%48, %49, %50, %51, %52, %53, %54, %55, %56, %57, %58, %59, %60, %61, %62, %63}, "
    "da, db, p, 1, 1, 0, 1;\n}"
    : "+f"(d[0]), "+f"(d[1]), "+f"(d[2]), "+f"(d[3]), "+f"(d[4]), "+f"(d[5]), "+f"(d[6]), "+f"(d[7]),
      "+f"(d[8]), "+f"(d[9]), "+f"(d[10]), "+f"(d[11]), "+f"(d[12]), "+f"(d[13]), "+f"(d[14]), "+f"(d[15]),
      "+f"(d[16]), "+f"(d[17]), "+f"(d[18]), "+f"(d[19]), "+f"(d[20]), "+f"(d[21]), "+f"(d[22]), "+f"(d[23]),
      "+f"(d[24]), "+f"(d[25]), "+f"(d[26]), "+f"(d[27]), "+f"(d[28]), "+f"(d[29]), "+f"(d[30]), "+f"(d[31]),
      "+f"(e[0]), "+f"(e[1]), "+f"(e[2]), "+f"(e[3]), "+f"(e[4]), "+f"(e[5]), "+f"(e[6]), "+f"(e[7]),
      "+f"(e[8]), "+f"(e[9]), "+f"(e[10]), "+f"(e[11]), "+f"(e[12]), "+f"(e[13]), "+f"(e[14]), "+f"(e[15]),
      "+f"(e[16]), "+f"(e[17]), "+f"(e[18]), "+f"(e[19]), "+f"(e[20]), "+f"(e[21]), "+f"(e[22]), "+f"(e[23]),
      "+f"(e[24]), "+f"(e[25]), "+f"(e[26]), "+f"(e[27]), "+f"(e[28]), "+f"(e[29]), "+f"(e[30]), "+f"(e[31])
    : "r"(la), "r"(lb), "n"(OA), "n"(OB), "n"(HA));
}
template <int OA, int OB, uint32_t HA>
__device__ __forceinline__ void wgmma_n176(float (&d)[88], uint32_t la, uint32_t lb) {
  asm volatile("{\n.reg .pred p;\n.reg .b32 ta, tb;\n.reg .b64 da, db;\n"
    "setp.eq.b32 p, 0, 0;\nadd.u32 ta, %88, %90;\nadd.u32 tb, %89, %91;\n"
    "mov.b64 da, {ta, %92};\nmov.b64 db, {tb, 0x40000040};\n"
    "wgmma.mma_async.sync.aligned.m64n176k16.f32.bf16.bf16 "
    "{%0, %1, %2, %3, %4, %5, %6, %7, %8, %9, %10, %11, %12, %13, %14, %15, "
    "%16, %17, %18, %19, %20, %21, %22, %23, %24, %25, %26, %27, %28, %29, %30, %31, "
    "%32, %33, %34, %35, %36, %37, %38, %39, %40, %41, %42, %43, %44, %45, %46, %47, "
    "%48, %49, %50, %51, %52, %53, %54, %55, %56, %57, %58, %59, %60, %61, %62, %63, "
    "%64, %65, %66, %67, %68, %69, %70, %71, %72, %73, %74, %75, %76, %77, %78, %79, "
    "%80, %81, %82, %83, %84, %85, %86, %87}, "
    "da, db, p, 1, 1, 0, 1;\n}"
    : "+f"(d[0]), "+f"(d[1]), "+f"(d[2]), "+f"(d[3]), "+f"(d[4]), "+f"(d[5]), "+f"(d[6]), "+f"(d[7]),
      "+f"(d[8]), "+f"(d[9]), "+f"(d[10]), "+f"(d[11]), "+f"(d[12]), "+f"(d[13]), "+f"(d[14]), "+f"(d[15]),
      "+f"(d[16]), "+f"(d[17]), "+f"(d[18]), "+f"(d[19]), "+f"(d[20]), "+f"(d[21]), "+f"(d[22]), "+f"(d[23]),
      "+f"(d[24]), "+f"(d[25]), "+f"(d[26]), "+f"(d[27]), "+f"(d[28]), "+f"(d[29]), "+f"(d[30]), "+f"(d[31]),
      "+f"(d[32]), "+f"(d[33]), "+f"(d[34]), "+f"(d[35]), "+f"(d[36]), "+f"(d[37]), "+f"(d[38]), "+f"(d[39]),
      "+f"(d[40]), "+f"(d[41]), "+f"(d[42]), "+f"(d[43]), "+f"(d[44]), "+f"(d[45]), "+f"(d[46]), "+f"(d[47]),
      "+f"(d[48]), "+f"(d[49]), "+f"(d[50]), "+f"(d[51]), "+f"(d[52]), "+f"(d[53]), "+f"(d[54]), "+f"(d[55]),
      "+f"(d[56]), "+f"(d[57]), "+f"(d[58]), "+f"(d[59]), "+f"(d[60]), "+f"(d[61]), "+f"(d[62]), "+f"(d[63]),
      "+f"(d[64]), "+f"(d[65]), "+f"(d[66]), "+f"(d[67]), "+f"(d[68]), "+f"(d[69]), "+f"(d[70]), "+f"(d[71]),
      "+f"(d[72]), "+f"(d[73]), "+f"(d[74]), "+f"(d[75]), "+f"(d[76]), "+f"(d[77]), "+f"(d[78]), "+f"(d[79]),
      "+f"(d[80]), "+f"(d[81]), "+f"(d[82]), "+f"(d[83]), "+f"(d[84]), "+f"(d[85]), "+f"(d[86]), "+f"(d[87])
    : "r"(la), "r"(lb), "n"(OA), "n"(OB), "n"(HA));
}

__device__ __forceinline__ void publish_stats(const uint32_t (&xr)[16], float2* dst  , int t, uint32_t tag) {
  float s0 = 0.f, s1 = 0.f;
#pragma unroll
  for (int j = 0; j < 8; j++) { s0 += bf_lo(xr[2 * j]) + bf_hi(xr[2 * j]); s1 += bf_lo(xr[2 * j + 1]) + bf_hi(xr[2 * j + 1]); }
  s0 += __shfl_xor_sync(0xffffffff, s0, 1); s1 += __shfl_xor_sync(0xffffffff, s1, 1);
  s0 += __shfl_xor_sync(0xffffffff, s0, 2); s1 += __shfl_xor_sync(0xffffffff, s1, 2);
  const float m0 = s0 * (1.f / 64.f), m1 = s1 * (1.f / 64.f);
  float q0 = 0.f, q1 = 0.f;
#pragma unroll
  for (int j = 0; j < 8; j++) {
    float a = bf_lo(xr[2 * j]) - m0, b = bf_hi(xr[2 * j]) - m0, c = bf_lo(xr[2 * j + 1]) - m1, d = bf_hi(xr[2 * j + 1]) - m1;
    q0 = fmaf(a, a, q0); q0 = fmaf(b, b, q0); q1 = fmaf(c, c, q1); q1 = fmaf(d, d, q1);
  }
  q0 += __shfl_xor_sync(0xffffffff, q0, 1); q1 += __shfl_xor_sync(0xffffffff, q1, 1);
  q0 += __shfl_xor_sync(0xffffffff, q0, 2); q1 += __shfl_xor_sync(0xffffffff, q1, 2);
  if (t < 2) st_relaxed_b64(dst + 8 * t, t ? s1 : s0, (__float_as_uint(t ? q1 : q0) & ~1u) | tag);
}

__device__ __forceinline__ void gather_stats(const float2* src  , uint32_t sm_dst, uint32_t bar, int lane, uint32_t tag) {
  const float2* p = src + lane * 2;
  float4 v[8];
  uint32_t cnt = 0;
  while (true) {
#pragma unroll
    for (int i = 0; i < 8; i++) v[i] = ld_relaxed_f4(p + i * 64);
    uint32_t bad = 0;
#pragma unroll
    for (int i = 0; i < 8; i++) bad |= (__float_as_uint(v[i].y) ^ tag) | (__float_as_uint(v[i].w) ^ tag);
    if (__all_sync(0xffffffff, (bad & 1u) == 0)) break;
    if (++cnt > SPIN_LIMIT) __trap();
    __nanosleep(100);
  }
  float sa = 0.f, sb = 0.f, qa = 0.f, qb = 0.f;
#pragma unroll
  for (int i = 0; i < 8; i++) { sa += v[i].x; qa += v[i].y; sb += v[i].z; qb += v[i].w; }
  const float ma = sa * (1.f / 512.f), mb = sb * (1.f / 512.f);
  float da = 0.f, db = 0.f;
#pragma unroll
  for (int i = 0; i < 8; i++) {
    const float a = v[i].x * (1.f / 64.f) - ma, b = v[i].z * (1.f / 64.f) - mb;
    da = fmaf(a, a, da); db = fmaf(b, b, db);
  }
  sts_f4(sm_dst + lane * 16, make_float4(rsqrtf(fmaf(da, 64.f, qa) * (1.f / 512.f) + 1e-5f), -ma, rsqrtf(fmaf(db, 64.f, qb) * (1.f / 512.f) + 1e-5f), -mb));
  __syncwarp();
  if (lane == 0) mbar_arrive(bar);
}

__device__ __forceinline__ void colsum_task(const __nv_bfloat16* p  , int pitch, bool ok, int row0, float4* dst  , int lane, uint32_t tag) {
  const int rg = lane >> 3;
  float a[8];
#pragma unroll
  for (int i = 0; i < 8; i++) a[i] = 0.f;
  if (ok) {
    uint4 v[8];
#pragma unroll
    for (int i = 0; i < 8; i++) v[i] = __ldg((const uint4*)(p + (size_t)(row0 + 4 * i + rg) * pitch));
#pragma unroll
    for (int i = 0; i < 8; i++) {
      a[0] += bf_lo(v[i].x); a[1] += bf_hi(v[i].x); a[2] += bf_lo(v[i].y); a[3] += bf_hi(v[i].y);
      a[4] += bf_lo(v[i].z); a[5] += bf_hi(v[i].z); a[6] += bf_lo(v[i].w); a[7] += bf_hi(v[i].w);
    }
  }
#pragma unroll
  for (int i = 0; i < 8; i++) { a[i] += __shfl_xor_sync(0xffffffff, a[i], 8); a[i] += __shfl_xor_sync(0xffffffff, a[i], 16); }
  if (rg == 0) {
    st_relaxed_f4(dst, a[0], a[1], a[2], (__float_as_uint(a[3]) & ~1u) | tag);
    st_relaxed_f4(dst + 1, a[4], a[5], a[6], (__float_as_uint(a[7]) & ~1u) | tag);
  }
}
__device__ __forceinline__ void colsum_gather(const float4* src, uint32_t sm_dst, int nunits, int lane, uint32_t tag) {
#pragma unroll 1
  for (int j = 0; j < 3; j++) {
    const float4* p = src + (lane >> 4) * 8 * 48 + j * 16 + (lane & 15);
    float4 v[8];
    uint32_t cnt = 0;
    while (true) {
      uint32_t bad = 0;
#pragma unroll
      for (int i = 0; i < 8; i++) v[i] = ld_relaxed_f4(p + i * 48);
#pragma unroll
      for (int i = 0; i < 8; i++) bad |= __float_as_uint(v[i].w) ^ tag;
      if (__all_sync(0xffffffff, (bad & 1u) == 0)) break;
      if (++cnt > SPIN_LIMIT) __trap();
    }
    float4 a = v[0];
#pragma unroll
    for (int i = 1; i < 8; i++) { a.x += v[i].x; a.y += v[i].y; a.z += v[i].z; a.w += v[i].w; }
    a.x += __shfl_xor_sync(0xffffffff, a.x, 16); a.y += __shfl_xor_sync(0xffffffff, a.y, 16);
    a.z += __shfl_xor_sync(0xffffffff, a.z, 16); a.w += __shfl_xor_sync(0xffffffff, a.w, 16);
    if (lane < 16 && j * 16 + lane < nunits) sts_f4(sm_dst + (j * 16 + lane) * 16, a);
  }
  __syncwarp();
}

__device__ __forceinline__ void wait_flag_acq(const uint32_t* f, uint32_t ev) {
  uint32_t cnt = 0;
  while ((int32_t)(ld_acquire(f) - ev) < 0) { if (++cnt > SPIN_LIMIT) __trap(); }
}
__device__ __forceinline__ void wait_flags(const uint32_t* f  , uint32_t ev) {
  uint32_t cnt = 0;
  while (!__all_sync(0xffffffff, (int32_t)(ld_relaxed(f) - ev) >= 0)) { if (++cnt > SPIN_LIMIT) __trap(); }
}
__device__ __forceinline__ void set_flags(uint4* flag  , uint32_t ev, int lane) {
  if (lane < 16) asm volatile("st.relaxed.gpu.global.v4.u32 [%0], {%1,%1,%1,%1};" :: "l"(flag + (lane >> 1) * 16 + (lane & 1)), "r"(ev) : "memory");
}
__device__ __forceinline__ void publish_chunk(uint4* gdst, uint32_t src, uint4* flag, uint32_t ev, int lane) {
  if (lane == 0) { bulk_s2g(gdst, src, 8192); bulk_commit(); bulk_wait<0>(); }
  __syncwarp();
  set_flags(flag, ev, lane);
}
__device__ __forceinline__ void order_before(int h) {
}
__device__ __forceinline__ void order_after(int h) {
}
__device__ __forceinline__ void fetch_chunks(const uint4* gbuf  , const uint4* flags, uint32_t abase, uint32_t afull, int r, uint32_t ev, int lane, int h) {
  wait_flags((const uint32_t*)(flags + r * 16 + (lane & 7) * 2), ev);
  order_before(h);
  if (elect_one()) {
#pragma unroll
    for (int i = 1; i < 8; i++) {
      mbar_expect_tx(afull + i * 8, 8192);
      bulk_g2s(abase + i * 8192, gbuf + ((r + i) & 7) * 512, 8192, afull + i * 8);
    }
  }
  __syncwarp();
  order_after(h);
}

__global__ void __cluster_dims__(2, 1, 1) __launch_bounds__(384, 1)
fused_kernel(const __grid_constant__ CUtensorMap tm_x, const __grid_constant__ CUtensorMap tm_out,
             const __grid_constant__ CUtensorMap tm_wqkv, const __grid_constant__ CUtensorMap tm_wo,
             const __grid_constant__ CUtensorMap tm_w1, const __grid_constant__ CUtensorMap tm_w2,
             const __nv_bfloat16* __restrict__ wqkv, const __nv_bfloat16* __restrict__ wo,
             const __nv_bfloat16* __restrict__ w1, const __nv_bfloat16* __restrict__ w2) {
  extern __shared__ __align__(1024) uint8_t smem_raw[];
  const uint32_t sb = smem_u32(smem_raw);
  const int warp = __shfl_sync(0xffffffff, threadIdx.x >> 5, 0);
  const int bid = __shfl_sync(0xffffffff, opaque(blockIdx.x), 0);
  int cb, r;
  {
    const int cl = bid >> 1;
    cb = cl >> 2; r = (cl & 3) * 2 + (bid & 1);
  }

  const int prof_id = cb * 8 + r; (void)prof_id;
  if (threadIdx.x == 0) {
    if (sb & 1023) __trap();
    for (int i = 0; i < 4; i++) { mbar_init(sb + B_BFULL + i * 8, 1); mbar_init(sb + B_BEMPTY + i * 8, 8); }
    for (int i = 0; i < 16; i++) mbar_init(sb + B_AFULL + i * 8, 1);
    for (int i = 0; i < 6; i++) { mbar_init(sb + B_AFREE + i * 8, 4); mbar_init(sb + B_OWN + i * 8, 4); }
    for (int i = 0; i < 2; i++) { mbar_init(sb + B_STAT + i * 8, 1); mbar_init(sb + B_PRDY + i * 8, 1); mbar_init(sb + B_PFREE + i * 8, 4); }
    mbar_init(sb + B_CSRDY, 1); mbar_init(sb + B_CSRDY + 8, 1); mbar_init(sb + B_KVDONE, 8); mbar_init(sb + B_KVRDY, 1);
    asm volatile("fence.mbarrier_init.release.cluster;" ::: "memory");
  }
  __syncthreads();
  asm volatile("barrier.cluster.arrive.relaxed.aligned;" ::: "memory");

  if (warp >= 8) {
  asm volatile("setmaxnreg.dec.sync.aligned.u32 96;");
  const int lane = __shfl_sync(0xffffffff, threadIdx.x & 31, threadIdx.x & 31);
  const uint32_t epoch = ld_relaxed(g_epoch + bid * 8);
  if (warp == 8) {
    uint32_t st = 0;
    auto acquire = [&](uint32_t bytes) -> uint32_t {
      const uint32_t s = st & 3;
      mbar_wait(sb + B_BEMPTY + s * 8, ((st >> 2) & 1) ^ 1);
      st++;
      return s;
    };
    if (lane == 0) { prefetch_map(&tm_wqkv); prefetch_map(&tm_wo); prefetch_map(&tm_w1); prefetch_map(&tm_w2); }
#pragma unroll 1
    for (int l = 0; l < 2; l++) {
#pragma unroll 1
      for (int i = 0; i < 8; i++) {
        const uint32_t s = acquire(0), dst = sb + SM_RING + s * SLOT, fb = sb + B_BFULL + s * 8;
        const int kc = (r + i) & 7;
        if (elect_one()) { mbar_expect_tx(fb, 16384); tma_load(dst, &tm_wqkv, 512 + 64 * r, 64 * kc, fb); tma_load(dst + 8192, &tm_wqkv, 1024 + 64 * r, 64 * kc, fb); }
      }
#pragma unroll 1
      for (int i = 0; i < 4; i++) {
        const uint32_t s = acquire(0), dst = sb + SM_RING + s * SLOT, fb = sb + B_BFULL + s * 8;
        if (elect_one()) { mbar_expect_tx(fb, 16384); tma_load(dst, &tm_wqkv, 64 * r, 64 * ((r + 2 * i) & 7), fb); tma_load(dst + 8192, &tm_wqkv, 64 * r, 64 * ((r + 2 * i + 1) & 7), fb); }
      }
#pragma unroll 1
      for (int i = 0; i < 4; i++) {
        const uint32_t s = acquire(0), dst = sb + SM_RING + s * SLOT, fb = sb + B_BFULL + s * 8;
        if (elect_one()) { mbar_expect_tx(fb, 16384); tma_load(dst, &tm_wo, 64 * r, 64 * ((r + 2 * i) & 7), fb); tma_load(dst + 8192, &tm_wo, 64 * r, 64 * ((r + 2 * i + 1) & 7), fb); }
      }
#pragma unroll 1
      for (int i = 0; i < 8; i++) {
        const uint32_t s = acquire(0), dst = sb + SM_RING + s * SLOT, fb = sb + B_BFULL + s * 8;
        const int kc = (r + i) & 7;
        if (elect_one()) { mbar_expect_tx(fb, 24576); tma_load(dst, &tm_w1, kHS * r, 64 * kc, fb); tma_load(dst + 8192, &tm_w1, kHS * r + 64, 64 * kc, fb); tma_load(dst + 16384, &tm_w1, kHS * r + 128, 64 * kc, fb); }
      }
#pragma unroll 1
      for (int i = 0; i < 8; i++) {
        const uint32_t s = acquire(0), dst = sb + SM_RING + s * SLOT, fb = sb + B_BFULL + s * 8;
        const int j = (r + (i & ~1)) & 7;
        if (elect_one()) { mbar_expect_tx(fb, kHS * 128); tma_load(dst, &tm_w2, 64 * ((i & 1) ? r : (r ^ 1)), kHS * j, fb); }
      }
    }
    asm volatile("barrier.cluster.wait.aligned;" ::: "memory");
  } else if (warp == 9 || warp == 10) {
    const int h = warp - 9, half0 = cb * 2 + h;
    if (elect_one()) {
      const uint32_t abase = sb + h * 65536, afull = sb + B_AFULL + h * 64;
      prefetch_map(&tm_x);
      for (int i = 0; i < 8; i++) { mbar_expect_tx(afull + i * 8, 8192); tma_load(abase + i * 8192, &tm_x, 64 * ((r + i) & 7), 128 * cb + 64 * h, afull + i * 8); }
    }
    __syncwarp();
    const uint32_t ev0 = epoch * 16, tag = (epoch + 1) & 1;
    set_flags(g_flags + half0 * 128 + r * 2, ev0, lane);
    colsum_task(wqkv + (1 + h) * 512 + 64 * r + 8 * (lane & 7), 3 * kD, true, 32 * cb, g_cs + ((r * 2 + 0) * 16 + cb) * 48 + (1 + h) * 16 + 2 * (lane & 7), lane, tag);
    gather_stats(g_stats + (0 * 32 + half0) * 512, sb + SM_STAT + h * 512, sb + B_STAT + h * 8, lane, tag);
#pragma unroll 1
    for (int b = h; b < 3; b += 2) {
      const int col = 64 * b + 8 * (lane & 7);
      colsum_task(w1 + kHS * r + col, kFF, col < kHS && kHS * r + col < kFF, 32 * cb, g_cs + ((r * 2 + 1) * 16 + cb) * 48 + b * 16 + 2 * (lane & 7), lane, tag);
    }
    asm volatile("barrier.cluster.wait.aligned;" ::: "memory");
    uint32_t p0 = 0;
#pragma unroll 1
    for (int l = 0; l < 2; l++) {
      const uint32_t ev = ev0 + l * 6;
      const int half = opaque(half0);
      const uint32_t abase = sb + h * 65536, afull = sb + B_AFULL + h * 64, afree = sb + B_AFREE + h * 24, own = sb + B_OWN + h * 24;
      uint4* flags = g_flags + half * 128;
      mbar_wait(own, p0);
      STAMP(2 + h, l * 16 + 0);
      publish_chunk(g_act + (0 * 32 + half) * 4096 + r * 512, abase, flags + r * 2, ev + 1, lane);
      STAMP(2 + h, l * 16 + 11);
      mbar_wait(afree, p0); p0 ^= 1;
      fetch_chunks(g_act + (0 * 32 + half) * 4096, flags, abase, afull, r, ev + 1, lane, h);
      STAMP(2 + h, l * 16 + 1);
      mbar_wait(own, p0);
      STAMP(2 + h, l * 16 + 2);
      publish_chunk(g_act + (1 * 32 + half) * 4096 + r * 512, abase, flags + r * 2, ev + 2, lane);
      mbar_wait(afree, p0); p0 ^= 1;
      STAMP(2 + h, l * 16 + 12);
      fetch_chunks(g_act + (1 * 32 + half) * 4096, flags, abase, afull, r, ev + 2, lane, h);
      STAMP(2 + h, l * 16 + 4);
      gather_stats(g_stats + ((2 * l + 1) * 32 + half) * 512, sb + SM_STAT + h * 512, sb + B_STAT + h * 8, lane, tag);
      STAMP(2 + h, l * 16 + 3);
      uint4* hb = g_h + half * 8 * 1536;
      mbar_wait(afree, p0);
      mbar_wait(own, p0); p0 ^= 1;
      STAMP(2 + h, l * 16 + 5);
      if (lane == 0) { bulk_s2g(hb + r * 1536, abase, 8192); bulk_commit(); }
      mbar_wait(own + 8, l);
      if (lane == 0) { bulk_s2g(hb + r * 1536 + 512, abase + 8192, 8192); bulk_commit(); }
      mbar_wait(own + 16, l);
      if (lane == 0) {
        bulk_s2g(hb + r * 1536 + 1024, abase + 16384, 6144); bulk_commit();
        bulk_wait<0>();
      }
      __syncwarp();
      set_flags(flags + r * 2, ev + 3, lane);
      STAMP(2 + h, l * 16 + 6);
      wait_flags((const uint32_t*)(flags + r * 16 + ((r + 2 * (lane & 3)) & 7) * 2), ev + 3);
      STAMP(2 + h, l * 16 + 13);
#pragma unroll 1
      for (int b = 3; b < 12; b++) {
        const int t = b / 3, bb = b - 3 * t, j = (r + 2 * t) & 7, slot = b & 7;
        if (b == 8) mbar_wait(afree + 8, l);
        if (b == 11) mbar_wait(afree + 16, l);
        if (elect_one()) {
          const uint32_t bytes = bb == 2 ? 6144 : 8192;
          mbar_expect_tx(afull + slot * 8, bytes);
          bulk_g2s(abase + slot * 8192, hb + j * 1536 + bb * 512, bytes, afull + slot * 8);
        }
        __syncwarp();
      }
      STAMP(2 + h, l * 16 + 7);
      mbar_wait(own, p0);
      STAMP(2 + h, l * 16 + 8);
      if (l == 0) {
        publish_chunk(g_act + (2 * 32 + half) * 4096 + r * 512, abase, flags + r * 2, ev + 6, lane);
        mbar_wait(afree, p0); p0 ^= 1;
        fetch_chunks(g_act + (2 * 32 + half) * 4096, flags, abase, afull, r, ev + 6, lane, h);
        STAMP(2 + h, l * 16 + 9);
        gather_stats(g_stats + (2 * 32 + half) * 512, sb + SM_STAT + h * 512, sb + B_STAT + h * 8, lane, tag);
      } else if (lane == 0) {
        tma_store(&tm_out, abase, 64 * r, 128 * cb + 64 * h); bulk_commit(); bulk_wait<0>();
      }
      STAMP(2 + h, l * 16 + 10);
    }
  } else {
    if (lane < 24) { g_kv[(0 * 8 + r) * 384 + cb * 24 + lane] = make_float4(0.f, 0.f, 0.f, 0.f); g_kv[(1 * 8 + r) * 384 + cb * 24 + lane] = make_float4(0.f, 0.f, 0.f, 0.f); }
    fence_gpu();
    const uint32_t tag = (epoch & 1) ^ 1;
    colsum_task(wqkv + 64 * r + 8 * (lane & 7), 3 * kD, true, 32 * cb, g_cs + ((r * 2 + 0) * 16 + cb) * 48 + 2 * (lane & 7), lane, tag);
    __nanosleep(500);
    colsum_gather(g_cs + (r * 2 + 0) * 16 * 48, sb + SM_CS, 48, lane, tag);
    fence_gpu();
    if (lane == 0) mbar_arrive(sb + B_CSRDY);
    STAMP(2, 48);
    if (lane == 1) prefetch_l2((const char*)wo + bid * 4096, 4096);
    if (lane == 2) prefetch_l2((const char*)w2 + bid * 11008, 11008);
    asm volatile("barrier.cluster.wait.aligned;" ::: "memory");
#pragma unroll 1
    for (int l = 0; l < 2; l++) {
      mbar_wait(sb + B_KVDONE, l);
      STAMP(2, 50 + l * 4);
      STAMP(2, 51 + l * 4);
      const float4* kv = g_kv + (l * 8 + r) * 384 + lane;
      float4 v[12];
      uint32_t cnt = 0;
      while (true) {
        bool ok = true;
#pragma unroll
        for (int i = 0; i < 12; i++) v[i] = ld_relaxed_f4(kv + i * 32);
#pragma unroll
        for (int i = 0; i < 12; i++) ok = ok && v[i].w == 32.f;
        if (__all_sync(0xffffffff, ok)) break;
        if (++cnt > SPIN_LIMIT) __trap();
      }
      STAMP(2, 52 + l * 4);
#pragma unroll
      for (int hh = 0; hh < 4; hh++) {
        const float4 a = v[3 * hh], b = v[3 * hh + 1], c = v[3 * hh + 2];
        const float z0 = __shfl_sync(0xffffffff, c.z, lane & 3), z1 = __shfl_sync(0xffffffff, c.z, 4 + (lane & 3)),
                    z2 = __shfl_sync(0xffffffff, c.z, 8 + (lane & 3)), z3 = __shfl_sync(0xffffffff, c.z, 12 + (lane & 3));
        const uint32_t d = sb + SM_RING + 16384 + hh * 768 + lane * 8;
        sts_u2(d, pack_bf16(a.x, a.y), pack_bf16(a.z, b.x));
        sts_u2(d + 256, pack_bf16(b.y, b.z), pack_bf16(c.x, c.y));
        sts_u2(d + 512, pack_bf16(z0, z1), pack_bf16(z2, z3));
      }
      __syncwarp();
      if (lane == 0) mbar_arrive(sb + B_KVRDY);
      STAMP(2, 53 + l * 4);
      if (l == 0) {
        colsum_gather(g_cs + (r * 2 + 1) * 16 * 48, sb + SM_CS + 768, 44, lane, tag);
        if (lane == 0) mbar_arrive(sb + B_CSRDY + 8);
      }
    }
    if (lane == 0) g_epoch[bid * 8] = epoch + 1;
  }
  } else {
    asm volatile("setmaxnreg.inc.sync.aligned.u32 200;");
    const int lane = __shfl_sync(0xffffffff, threadIdx.x & 31, threadIdx.x & 31);
    const uint32_t epoch = ld_relaxed(g_epoch + bid * 8);
    const int wg0 = warp >> 2, lane0 = lane, half = cb * 2 + wg0, wg = wg0;
    const uint32_t sb0 = sb;
    STAMP(wg, 62);
    const uint32_t tag = (epoch + 1) & 1;
    uint32_t xr[16];
    uint32_t sph = 0;
    mbar_wait(sb0 + B_AFULL + wg0 * 64, 0);
#pragma unroll
    for (int s = 0; s < 4; s++)
      ldsm4(sb0 + wg0 * 65536 + (16 * (warp & 3) + 8 * ((lane0 >> 3) & 1) + (lane0 & 7)) * 128 + (((2 * s + (lane0 >> 4)) ^ (lane0 & 7)) << 4),
            xr[4 * s], xr[4 * s + 1], xr[4 * s + 2], xr[4 * s + 3]);
    asm volatile("barrier.cluster.wait.aligned;" ::: "memory");
    STAMP(wg, 63);

#pragma unroll 1
    for (int l = 0; l < 2; l++) {
      const uint32_t sb = opaque(sb0);
      const int lane = opaque(lane0), wg = opaque(wg0), wq = opaque(warp) & 3, g = lane >> 2, t = lane & 3;
      const uint32_t abase = sb + wg * 65536, afull = sb + B_AFULL + wg * 64, afree = sb + B_AFREE + wg * 24, own = sb + B_OWN + wg * 24;
      const uint32_t ring = sb + SM_RING;
      const uint32_t dA = desc_lo(abase, 16), dH = desc_lo(abase, 1024), dB = desc_lo(ring, 8192), dB2 = desc_lo(ring, SLOT);
      constexpr int S4 = SLOT >> 4;
      uint32_t swa[4];
#pragma unroll
      for (int s = 0; s < 4; s++) swa[s] = abase + (16 * wq + 8 * ((lane >> 3) & 1) + (lane & 7)) * 128 + (((2 * s + (lane >> 4)) ^ (lane & 7)) << 4);
      auto wait_b = [&](int st) { mbar_wait(sb + B_BFULL + (st & 3) * 8, (st >> 2) & 1); };
      auto release_b = [&](int st) { if (lane == 0) mbar_arrive(sb + B_BEMPTY + (st & 3) * 8); };
      auto signal = [&](uint32_t bar) { __syncwarp(); if (lane == 0) mbar_arrive(bar); };
      const uint32_t chk = abase + (16 * wq + g) * 128 + (((2 * t) ^ g) << 4);
      auto bad_chunk = [&](int i, uint32_t tg) -> uint32_t { return (lds_u32(chk + i * 8192) ^ tg) | (lds_u32(chk + (i * 8192 + 1024)) ^ tg); };
      auto fetch_ok = [&](int i, int n, uint32_t par, uint32_t par3  , int buf, uint32_t tg) {
        uint32_t bad = 0;
#pragma unroll
        for (int u = i; u < i + n; u++) mbar_wait(afull + u * 8, u == 3 ? par3 : par);
#pragma unroll
        for (int u = i; u < i + n; u++) bad |= bad_chunk(u, tg);
        if (!NOCHECK && __builtin_expect(!__all_sync(0xffffffff, (bad & 1u) == 0), 0)) {
#pragma unroll 1
          for (int u = i; u < i + n; u++) {
            const uint4* src = g_act + (buf * 32 + opaque(half)) * 4096 + ((opaque(r) + u) & 7) * 512 + wq * 128 + opaque(lane);
            const uint32_t dst = abase + u * 8192 + wq * 2048 + opaque(lane) * 16;
            uint32_t cnt = 0;
            while (!__all_sync(0xffffffff, (bad_chunk(u, tg) & 1u) == 0)) {
#pragma unroll 1
              for (int v = 0; v < 4; v++) sts_u4(dst + v * 512, ld_relaxed_u4(src + v * 32));
              fence_async_smem();
              __syncwarp();
              if (++cnt > SPIN_LIMIT) __trap();
            }
          }
        }
      };
      const uint32_t hchk = abase + (lane >> 4) * 2048 + ((lane >> 3) & 1) * 1024 + (2 * wq + ((lane >> 2) & 1)) * 128 + (lane & 3) * 32 + g * 4;
      const uint32_t hchk3 = hchk + (lane >= 16 ? 0 : 4096);
      auto bad_block = [&](int b, uint32_t tg) -> uint32_t {
        return (lds_u32(hchk + (b & 7) * 8192) ^ tg) | (lds_u32(b % 3 == 2 ? hchk3 + (b & 7) * 8192 : hchk + ((b & 7) * 8192 + 4096)) ^ tg);
      };
      auto fetch_h_ok = [&](int b, int n, uint32_t tg) {
        uint32_t bad = 0;
#pragma unroll
        for (int u = b; u < b + n; u++) mbar_wait(afull + (u & 7) * 8, (u == 3 || u == 8) ? (l ^ 1) : u == 11 ? l : 1);
#pragma unroll
        for (int u = b; u < b + n; u++) bad |= bad_block(u, tg);
        if (!NOCHECK && __builtin_expect(!__all_sync(0xffffffff, (bad >> 31) == 0), 0)) {
#pragma unroll 1
          for (int u = b; u < b + n; u++) {
            const int ln = opaque(lane);
            const uint32_t off = (ln >> 4) * 1024 + wq * 256 + (ln & 15) * 16;
            const uint4* src = g_h + (opaque(half) * 8 + ((opaque(r) + 2 * (u / 3)) & 7)) * 1536 + (u % 3) * 512 + off / 16;
            uint32_t cnt = 0;
            while (!__all_sync(0xffffffff, (bad_block(u, tg) >> 31) == 0)) {
#pragma unroll 1
              for (int v = 0; v < (u % 3 == 2 ? 3 : 4); v++) sts_u4(abase + (u & 7) * 8192 + v * 2048 + off, ld_relaxed_u4(src + v * 128));
              fence_async_smem();
              __syncwarp();
              if (++cnt > SPIN_LIMIT) __trap();
            }
          }
        }
      };
      const uint32_t tmask = t == 0 ? 1u : 0u;
      auto store_chunk = [&](const uint32_t (&v)[16], uint32_t tg  , uint32_t msk) {
#pragma unroll
        for (int s = 0; s < 4; s++) stsm4(swa[s], (v[4 * s] & ~msk) | tg, (v[4 * s + 1] & ~msk) | tg, v[4 * s + 2], v[4 * s + 3]);
        fence_async_smem();
        signal(own);
      };
      auto stat_dst = [&](int ln) -> float2* { return g_stats + (ln * 32 + opaque(half)) * 512 + opaque(r) * 64 + 16 * wq + g; };
      const uint32_t stat_sm = sb + SM_STAT + (wg * 64 + 16 * wq + g) * 8;
      const uint32_t cs_sm = sb + SM_CS + 8 * t;
      const uint32_t ltag = l ^ 1;
      float rs0, rs1;
      {
        float ak[32], av[32], aq[32];
        STAMP(wg, l * 24 + 0);
        {
          wait_b(0);
          wg_fence();
          wgmma_n128_init<0, 0, HI_SW>(ak, av, dA, dB);
          static_for<1, 4>([&](auto K) { wgmma_n128<2 * K.value, 128 * K.value, HI_SW>(ak, av, dA, dB); });
          wg_commit();
          publish_stats(xr, stat_dst(2 * l), t, tag);
        }
        static_for<1, 8>([&](auto I) {
          constexpr int i = I.value;
          if (l == 0) mbar_wait(afull + i * 8, 0); else fetch_ok(i, 1, 0, 1, 2, tag);
          if (i == 1) STAMP(wg, l * 2 + 19);
          wait_b(i);
          wg_fence_in();
          static_for<0, 4>([&](auto K) { wgmma_n128<i * 512 + 2 * K.value, (i & 3) * S4 + 128 * K.value, HI_SW>(ak, av, dA, dB); });
          wg_commit();
          wg_wait<1>(); release_b(i - 1);
        });
        STAMP(wg, l * 24 + 1);
        auto q_stage = [&](auto I) {
          constexpr int i = I.value;
          wait_b(8 + i);
          wg_fence();
          static_for<0, 8>([&](auto K) {
            constexpr int k = K.value;
            if constexpr (i == 0 && k == 0) wgmma_n64_init<0, 0, HI_SW>(aq, dA, dB);
            else wgmma_n64<i * 1024 + (k >> 2) * 512 + 2 * (k & 3), i * S4 + 128 * k, HI_SW>(aq, dA, dB);
          });
          wg_commit();
        };
        if (l == 0) mbar_wait(sb + B_CSRDY, 0);
        mbar_wait(sb + B_STAT + wg * 8, sph); sph ^= 1;
        const float2 s0 = lds_f2(stat_sm), s1 = lds_f2(stat_sm + 64);
        const float y0 = s0.x * 1.4426950408889634f, y1 = s1.x * 1.4426950408889634f;
        const uint32_t pk_s = ring + (2 * wg) * SLOT + 16384, v_s = ring + (2 * wg + 1) * SLOT + 16384;
        {
          float2 c[16];
#pragma unroll
          for (int j = 0; j < 16; j++) c[j] = lds_f2(cs_sm + (64 + 8 * j) * 4);
          wg_wait<0>(); release_b(7);
          fence_regs(ak); fence_regs(av);
          STAMP(wg, l * 24 + 2);
          uint32_t pk[16], pv[16];
#pragma unroll
          for (int j = 0; j < 8; j++) {
            pk[2 * j] = pack_bf16(phi_y(y0 * fmaf(s0.y, c[j].x, ak[4 * j])), phi_y(y0 * fmaf(s0.y, c[j].y, ak[4 * j + 1])));
            pk[2 * j + 1] = pack_bf16(phi_y(y1 * fmaf(s1.y, c[j].x, ak[4 * j + 2])), phi_y(y1 * fmaf(s1.y, c[j].y, ak[4 * j + 3])));
            pv[2 * j] = pack_bf16(s0.x * fmaf(s0.y, c[8 + j].x, av[4 * j]), s0.x * fmaf(s0.y, c[8 + j].y, av[4 * j + 1]));
            pv[2 * j + 1] = pack_bf16(s1.x * fmaf(s1.y, c[8 + j].x, av[4 * j + 2]), s1.x * fmaf(s1.y, c[8 + j].y, av[4 * j + 3]));
          }
#pragma unroll
          for (int s = 0; s < 4; s++) {
            stsm4(swa[s] + (pk_s - abase), pk[4 * s], pk[4 * s + 1], pk[4 * s + 2], pk[4 * s + 3]);
            stsm4(swa[s] + (pk_s - abase) + SLOT, pv[4 * s], pv[4 * s + 1], pv[4 * s + 2], pv[4 * s + 3]);
          }
        }
        wg_bar(wg);
        {
          float c0[4] = {0.f, 0.f, 0.f, 0.f}, c1[4] = {0.f, 0.f, 0.f, 0.f}, z0[4] = {0.f, 0.f, 0.f, 0.f}, z1[4] = {0.f, 0.f, 0.f, 0.f};
          const int m = lane >> 3;
#pragma unroll
          for (int ks = 0; ks < 4; ks++) {
            uint32_t a0, a1, a2, a3, b0, b1, b2, b3;
            const int ra = 16 * ks + 8 * (m >> 1) + (lane & 7), rb = 16 * ks + 8 * (m & 1) + (lane & 7);
            ldsm4t(v_s + ra * 128 + (((2 * wq + (m & 1)) ^ (lane & 7)) << 4), a0, a1, a2, a3);
            ldsm4t(pk_s + rb * 128 + (((2 * wq + (m >> 1)) ^ (lane & 7)) << 4), b0, b1, b2, b3);
            mma16816(c0, a0, a1, a2, a3, b0, b1);
            mma16816(c1, a0, a1, a2, a3, b2, b3);
            mma16816(z0, 0x3f803f80u, 0x3f803f80u, 0x3f803f80u, 0x3f803f80u, b0, b1);
            mma16816(z1, 0x3f803f80u, 0x3f803f80u, 0x3f803f80u, 0x3f803f80u, b2, b3);
          }
          float* kv = (float*)(g_kv + (l * 8 + opaque(r)) * 384 + wq * 96 + lane);
          red_add_f4(kv, c0[0], c0[1], c1[0], 1.f);
          red_add_f4(kv + 128, c1[1], c0[2], c0[3], 1.f);
          red_add_f4(kv + 256, c1[2], c1[3], g == 0 ? z0[0] : g == 1 ? z0[1] : g == 2 ? z1[0] : z1[1], 1.f);
          signal(sb + B_KVDONE);
        }
        STAMP(wg, l * 24 + 3);
        q_stage(IC<0>{}); q_stage(IC<1>{}); q_stage(IC<2>{}); q_stage(IC<3>{});
        float2 c[8];
#pragma unroll
        for (int j = 0; j < 8; j++) c[j] = lds_f2(cs_sm + 8 * j * 4);
        wg_wait<3>(); release_b(8);
        wg_wait<2>(); release_b(9);
        wg_wait<1>(); release_b(10);
        wg_wait<0>(); release_b(11);
        fence_regs(aq);
        if (lane == 0) mbar_arrive(afree);
        STAMP(wg, l * 24 + 4);
        uint32_t pq[16];
#pragma unroll
        for (int j = 0; j < 8; j++) {
          pq[2 * j] = pack_bf16(phi_y(y0 * fmaf(s0.y, c[j].x, aq[4 * j])), phi_y(y0 * fmaf(s0.y, c[j].y, aq[4 * j + 1])));
          pq[2 * j + 1] = pack_bf16(phi_y(y1 * fmaf(s1.y, c[j].x, aq[4 * j + 2])), phi_y(y1 * fmaf(s1.y, c[j].y, aq[4 * j + 3])));
        }
        STAMP(wg, l * 24 + 5);
        mbar_wait(sb + B_KVRDY, l);
        STAMP(wg, l * 24 + 6);
        uint2 f[12];
#pragma unroll
        for (int i = 0; i < 12; i++) f[i] = lds_u2(ring + 16384 + i * 256 + lane * 8);
        float cn[4][8], cz[4][4];
#pragma unroll
        for (int hh = 0; hh < 4; hh++) {
          float c0[4] = {0.f, 0.f, 0.f, 0.f}, c1[4] = {0.f, 0.f, 0.f, 0.f};
          cz[hh][0] = cz[hh][1] = cz[hh][2] = cz[hh][3] = 0.f;
          mma16816(cz[hh], pq[4 * hh], pq[4 * hh + 1], pq[4 * hh + 2], pq[4 * hh + 3], f[3 * hh + 2].x, f[3 * hh + 2].y);
          mma16816(c0, pq[4 * hh], pq[4 * hh + 1], pq[4 * hh + 2], pq[4 * hh + 3], f[3 * hh].x, f[3 * hh].y);
          mma16816(c1, pq[4 * hh], pq[4 * hh + 1], pq[4 * hh + 2], pq[4 * hh + 3], f[3 * hh + 1].x, f[3 * hh + 1].y);
#pragma unroll
          for (int u = 0; u < 4; u++) { cn[hh][u] = c0[u]; cn[hh][4 + u] = c1[u]; }
        }
        uint32_t o[16];
#pragma unroll
        for (int hh = 0; hh < 4; hh++) {
          const float i0 = rcp(cz[hh][0] + 1e-6f), i1 = rcp(cz[hh][2] + 1e-6f);
          o[4 * hh] = pack_bf16(cn[hh][0] * i0, cn[hh][1] * i0); o[4 * hh + 1] = pack_bf16(cn[hh][2] * i1, cn[hh][3] * i1);
          o[4 * hh + 2] = pack_bf16(cn[hh][4] * i0, cn[hh][5] * i0); o[4 * hh + 3] = pack_bf16(cn[hh][6] * i1, cn[hh][7] * i1);
        }
        store_chunk(o, ltag & tmask, tmask);
        wg_bar(wg);
        STAMP(wg, l * 24 + 7);
      }
      {
        float acc[32];
        {
          wait_b(12);
          wg_fence();
          wgmma_n64_init<0, 0, HI_SW>(acc, dA, dB);
          static_for<1, 4>([&](auto K) { wgmma_n64<2 * K.value, 128 * K.value, HI_SW>(acc, dA, dB); });
          wg_commit();
        }
        static_for<1, 8>([&](auto I) {
          constexpr int i = I.value;
          if ((i & 1) == 0) wait_b(12 + i / 2);
          if (i == 1 || (i & 1) == 0) fetch_ok(i, i == 1 ? 1 : 2, 1, ltag, 0, ltag);
          if (i == 1) STAMP(wg, l * 24 + 8);
          if (l == 1) STAMP(wg, 43 + i);
          wg_fence_in();
          static_for<0, 4>([&](auto K) { wgmma_n64<i * 512 + 2 * K.value, (i / 2) * S4 + (i & 1) * 512 + 128 * K.value, HI_SW>(acc, dA, dB); });
          wg_commit();
          if ((i & 1) == 0) { wg_wait<1>(); release_b(11 + i / 2); }
        });
        wg_wait<0>(); release_b(15);
        fence_regs(acc);
        if (lane == 0) mbar_arrive(afree);
        STAMP(wg, l * 24 + 9);
#pragma unroll
        for (int j = 0; j < 8; j++) {
          xr[2 * j] = pack_bf16(bf_lo(xr[2 * j]) + acc[4 * j], bf_hi(xr[2 * j]) + acc[4 * j + 1]);
          xr[2 * j + 1] = pack_bf16(bf_lo(xr[2 * j + 1]) + acc[4 * j + 2], bf_hi(xr[2 * j + 1]) + acc[4 * j + 3]);
        }
        store_chunk(xr, ltag & tmask, tmask);
        wg_bar(wg);
        STAMP(wg, l * 24 + 10);
      }
      {
        float acc[88];
        {
          wait_b(16);
          wg_fence();
          wgmma_n176_init<0, 0, HI_SW>(acc, dA, dB);
          static_for<1, 4>([&](auto K) { wgmma_n176<2 * K.value, 128 * K.value, HI_SW>(acc, dA, dB); });
          wg_commit();
          publish_stats(xr, stat_dst(2 * l + 1), t, tag);
        }
        static_for<1, 8>([&](auto I) {
          constexpr int i = I.value;
          fetch_ok(i, 1, 0, l, 1, ltag);
          if (i == 1) STAMP(wg, l * 24 + 11);
          wait_b(16 + i);
          wg_fence_in();
          static_for<0, 4>([&](auto K) { wgmma_n176<i * 512 + 2 * K.value, (i & 3) * S4 + 128 * K.value, HI_SW>(acc, dA, dB); });
          wg_commit();
          wg_wait<1>(); release_b(15 + i);
        });
        if (l == 0) mbar_wait(sb + B_CSRDY + 8, 0);
        mbar_wait(sb + B_STAT + wg * 8, sph); sph ^= 1;
        const float2 s0 = lds_f2(stat_sm), s1 = lds_f2(stat_sm + 64);
        float2 c[22];
#pragma unroll
        for (int j = 0; j < 22; j++) c[j] = lds_f2(cs_sm + (192 + 8 * j) * 4);
        const uint32_t sgn = ltag ? 0x80008000u : 0u;
        rs0 = ltag ? -s0.x : s0.x; rs1 = ltag ? -s1.x : s1.x;
        wg_wait<0>(); release_b(23);
        fence_regs(acc);
        if (lane == 0) mbar_arrive(afree);
        STAMP(wg, l * 24 + 12);
        const uint32_t hrow = abase + (lane >> 4) * 1024 + (2 * wq + ((lane >> 3) & 1)) * 128 + (lane & 7) * 16;
#pragma unroll
        for (int b = 0; b < 3; b++) {
          uint32_t p[16];
#pragma unroll
          for (int u = 0; u < (b == 2 ? 6 : 8); u++) {
            const int j = 8 * b + u;
            p[2 * u] = pack_bf16_relu(fmaf(s0.y, c[j].x, acc[4 * j]), fmaf(s0.y, c[j].y, acc[4 * j + 1])) ^ sgn;
            p[2 * u + 1] = pack_bf16_relu(fmaf(s1.y, c[j].x, acc[4 * j + 2]), fmaf(s1.y, c[j].y, acc[4 * j + 3])) ^ sgn;
          }
#pragma unroll
          for (int s = 0; s < (b == 2 ? 3 : 4); s++) stsm4(hrow + (4 * b + s) * 2048, p[4 * s], p[4 * s + 1], p[4 * s + 2], p[4 * s + 3]);
          fence_async_smem(); signal(own + b * 8);
        }
        wg_bar(wg);
        STAMP(wg, l * 24 + 13);
      }
      {
        float ap[32], ao[32];
        float bp[32], bo[32];
        const uint32_t htag = ltag << 31;
        {
          wait_b(24); wait_b(25);
          wg_fence();
          wgmma_n128_init<0, 0, HI_NS>(ap, ao, dH, dB2);
          static_for<1, 11>([&](auto K) { wgmma_n128<128 * K.value, 128 * K.value, HI_NS>(ap, ao, dH, dB2); });
          wg_commit();
          wg_wait<0>(); release_b(24); release_b(25);
          if (lane == 0) mbar_arrive(afree + 8);
        }
        static_for<1, 3>([&](auto TT) {
          constexpr int tt = TT.value;
          wait_b(24 + 2 * tt); wait_b(25 + 2 * tt);
          static_for<0, 3>([&](auto BB) {
            constexpr int bb = BB.value, slot = (3 * tt + bb) & 7;
            fetch_h_ok(3 * tt + bb, 1, htag);
            if (tt == 1 && bb == 0) STAMP(wg, l * 24 + 14);
            if (l == 1) STAMP(wg, 48 + 3 * tt + bb);
            wg_fence_in();
            static_for<0, (bb == 2 ? 3 : 4)>([&](auto K) { wgmma_n128<slot * 512 + 128 * K.value, ((2 * tt) & 3) * S4 + 128 * (4 * bb + K.value), HI_NS>(ap, ao, dH, dB2); });
            wg_commit();
            if (bb == 0 && tt == 2) {
              wg_wait<1>(); release_b(22 + 2 * tt); release_b(23 + 2 * tt);
              if (lane == 0) mbar_arrive(afree + 8 * tt);
              if (lane == 0) { mbar_arrive_remote(mapa(sb + B_PFREE + wg * 8, (r & 1) ^ 1)); if (wq == 0) mbar_expect_tx(sb + B_PRDY + wg * 8, 8192); }
            }
          });
        });
        {
          wait_b(30);
          static_for<0, 3>([&](auto BB) {
            constexpr int bb = BB.value;
            if (bb == 0) fetch_h_ok(9, 3, htag);
            if (l == 1) STAMP(wg, 57 + bb);
            if (bb == 0) wg_fence(); else wg_fence_in();
            static_for<0, (bb == 2 ? 3 : 4)>([&](auto K) {
              if constexpr (bb == 0 && K.value == 0) wgmma_n64_init<512, 2 * S4, HI_NS>(bp, dH, dB2);
              else wgmma_n64<(1 + bb) * 512 + 128 * K.value, 2 * S4 + 128 * (4 * bb + K.value), HI_NS>(bp, dH, dB2);
            });
            wg_commit();
            if (bb == 0) { wg_wait<1>(); release_b(28); release_b(29); }
          });
          wait_b(31);
          wg_fence();
          wgmma_n64_init<512, 3 * S4, HI_NS>(bo, dH, dB2);
          static_for<1, 11>([&](auto K) { wgmma_n64<512 + 128 * K.value, 3 * S4 + 128 * K.value, HI_NS>(bo, dH, dB2); });
          wg_commit();
          wg_wait<1>(); release_b(30);
          fence_regs(ap); fence_regs(ao); fence_regs(bp);
          STAMP(wg, l * 24 + 15);
          mbar_wait(sb + B_PFREE + wg * 8, l);
          const uint32_t rdst = mapa(abase + 4 * 8192 + (wq * 32 + lane) * 16, (r & 1) ^ 1), rbar = mapa(sb + B_PRDY + wg * 8, (r & 1) ^ 1);
#pragma unroll
          for (int i = 0; i < 4; i++)
            st_async_v4(rdst + i * 2048, pack_bf16(ap[8 * i] + bp[8 * i], ap[8 * i + 1] + bp[8 * i + 1]), pack_bf16(ap[8 * i + 2] + bp[8 * i + 2], ap[8 * i + 3] + bp[8 * i + 3]),
                        pack_bf16(ap[8 * i + 4] + bp[8 * i + 4], ap[8 * i + 5] + bp[8 * i + 5]), pack_bf16(ap[8 * i + 6] + bp[8 * i + 6], ap[8 * i + 7] + bp[8 * i + 7]), rbar);
          wg_wait<0>(); release_b(31);
          fence_regs(bo);
#pragma unroll
          for (int i = 0; i < 32; i++) ao[i] += bo[i];
          STAMP(wg, l * 24 + 16);
          mbar_wait(sb + B_PRDY + wg * 8, l);
          STAMP(wg, l * 24 + 17);
          uint4 p[4];
#pragma unroll
          for (int i = 0; i < 4; i++) p[i] = lds_u4(abase + 4 * 8192 + i * 2048 + (wq * 32 + lane) * 16);
#pragma unroll
          for (int i = 0; i < 4; i++) {
            xr[4 * i] = pack_bf16(fmaf(rs0, ao[8 * i] + bf_lo(p[i].x), bf_lo(xr[4 * i])), fmaf(rs0, ao[8 * i + 1] + bf_hi(p[i].x), bf_hi(xr[4 * i])));
            xr[4 * i + 1] = pack_bf16(fmaf(rs1, ao[8 * i + 2] + bf_lo(p[i].y), bf_lo(xr[4 * i + 1])), fmaf(rs1, ao[8 * i + 3] + bf_hi(p[i].y), bf_hi(xr[4 * i + 1])));
            xr[4 * i + 2] = pack_bf16(fmaf(rs0, ao[8 * i + 4] + bf_lo(p[i].z), bf_lo(xr[4 * i + 2])), fmaf(rs0, ao[8 * i + 5] + bf_hi(p[i].z), bf_hi(xr[4 * i + 2])));
            xr[4 * i + 3] = pack_bf16(fmaf(rs1, ao[8 * i + 6] + bf_lo(p[i].w), bf_lo(xr[4 * i + 3])), fmaf(rs1, ao[8 * i + 7] + bf_hi(p[i].w), bf_hi(xr[4 * i + 3])));
          }
          signal(afree);
          store_chunk(xr, l == 0 ? (tag & tmask) : 0u, l == 0 ? tmask : 0u);
          wg_bar(wg);
          STAMP(wg, l * 24 + 18);
        }
      }
      if (l == 0) asm volatile("" ::: "memory");
    }

  }
}

typedef CUresult (*EncodeFn)(CUtensorMap*, CUtensorMapDataType, cuuint32_t, void*, const cuuint64_t*, const cuuint64_t*, const cuuint32_t*,
                             const cuuint32_t*, CUtensorMapInterleave, CUtensorMapSwizzle, CUtensorMapL2promotion, CUtensorMapFloatOOBfill);

CUtensorMap make_map(EncodeFn enc, const void* ptr, uint64_t cols, uint64_t rows, uint32_t box_rows) {
  CUtensorMap m;
  cuuint64_t gd[2] = {cols, rows}, gs[1] = {cols * 2};
  cuuint32_t bd[2] = {64, box_rows}, es[2] = {1, 1};
  enc(&m, CU_TENSOR_MAP_DATA_TYPE_BFLOAT16, 2, const_cast<void*>(ptr), gd, gs, bd, es, CU_TENSOR_MAP_INTERLEAVE_NONE,
      CU_TENSOR_MAP_SWIZZLE_128B, CU_TENSOR_MAP_L2_PROMOTION_L2_128B, CU_TENSOR_MAP_FLOAT_OOB_FILL_NONE);
  return m;
}

}

extern "C" void kernel_launch(void* const* d_in, const int* in_sizes, int n_in, void* d_out, int out_size) {
  (void)in_sizes; (void)n_in; (void)out_size;
  const __nv_bfloat16* x = (const __nv_bfloat16*)d_in[0];
  const __nv_bfloat16* wqkv = (const __nv_bfloat16*)d_in[1];
  const __nv_bfloat16* wo = (const __nv_bfloat16*)d_in[2];
  const __nv_bfloat16* w1 = (const __nv_bfloat16*)d_in[4];
  const __nv_bfloat16* w2 = (const __nv_bfloat16*)d_in[5];
  void* fn = nullptr;
  cudaDriverEntryPointQueryResult q;
  cudaGetDriverEntryPoint("cuTensorMapEncodeTiled", &fn, cudaEnableDefault, &q);
  EncodeFn enc = (EncodeFn)fn;
  const CUtensorMap tm_x = make_map(enc, x, kD, kS, 64), tm_out = make_map(enc, d_out, kD, kS, 64),
                    tm_wqkv = make_map(enc, wqkv, 3 * kD, kD, 64), tm_wo = make_map(enc, wo, kD, kD, 64),
                    tm_w1 = make_map(enc, w1, kFF, kD, 64), tm_w2 = make_map(enc, w2, kD, kFF, kHS);
  cudaFuncSetAttribute(fused_kernel, cudaFuncAttributeMaxDynamicSharedMemorySize, SM_TOTAL);
  fused_kernel<<<128, 384, SM_TOTAL>>>(tm_x, tm_out, tm_wqkv, tm_wo, tm_w1, tm_w2, wqkv, wo, w1, w2);
}
```

```cpp
#include <cuda_runtime.h>
#include <cuda_bf16.h>
#include <cuda.h>
#include <stdint.h>

#define NOCHECK 0
#define NOFENCE 0
#define KVSLEEP 40
#define KVDELAY 600
#define PUBWAIT bulk_wait_read
#define NLL 2
#define PRIO 0
#define MAPPING 0
namespace {

constexpr int kS = 2048, kD = 512, kFF = 1376, kHS = 176;
constexpr uint32_t SM_RING = 131072, SLOT = 24576, SM_MISC = 229376;
constexpr uint32_t SM_STAT = SM_MISC;
constexpr uint32_t SM_CS = SM_MISC + 1024;
constexpr uint32_t SM_BAR = SM_CS + 1472;
constexpr uint32_t B_BFULL = SM_BAR, B_BEMPTY = SM_BAR + 32, B_AFULL = SM_BAR + 64  ,
                   B_AFREE = SM_BAR + 192  , B_OWN = SM_BAR + 240  , B_STAT = SM_BAR + 288  ,
                   B_CSRDY = SM_BAR + 304  , B_KVDONE = SM_BAR + 320, B_KVRDY = SM_BAR + 328,
                   B_PRDY = SM_BAR + 336  , B_PFREE = SM_BAR + 352  ;
constexpr uint32_t SM_TOTAL = SM_BAR + 368;
static_assert(SM_TOTAL <= 232448, "smem");
constexpr uint32_t SPIN_LIMIT = 1u << 22;

__device__ uint32_t g_epoch[128 * 8];
__device__ __align__(128) uint4 g_flags[32 * 8 * 8 * 8];
__device__ __align__(16) float4 g_cs[8 * 2 * 16 * 48];
__device__ __align__(128) float4 g_kv[2 * 8 * 384];
__device__ __align__(128) float2 g_stats[4 * 32 * 64 * 8];
__device__ __align__(1024) uint4 g_act[3 * 32 * 8 * 512];
__device__ __align__(1024) uint4 g_h[32 * 8 * 3 * 512];
#define HEALCNT() do {} while (0)
#define STAMP(role, i) do {} while (0)

__device__ __forceinline__ uint32_t smem_u32(const void* p) { return (uint32_t)__cvta_generic_to_shared(p); }
__device__ __forceinline__ void mbar_init(uint32_t bar, uint32_t cnt) { asm volatile("mbarrier.init.shared::cta.b64 [%0], %1;" :: "r"(bar), "r"(cnt)); }
__device__ __forceinline__ void mbar_expect_tx(uint32_t bar, uint32_t bytes) { asm volatile("mbarrier.arrive.expect_tx.shared::cta.b64 _, [%0], %1;" :: "r"(bar), "r"(bytes) : "memory"); }
__device__ __forceinline__ void mbar_arrive(uint32_t bar) { asm volatile("mbarrier.arrive.shared::cta.b64 _, [%0];" :: "r"(bar) : "memory"); }
__device__ __forceinline__ void mbar_arrive_remote(uint32_t bar) { asm volatile("mbarrier.arrive.shared::cluster.b64 _, [%0];" :: "r"(bar) : "memory"); }
__device__ __forceinline__ void mbar_wait(uint32_t bar, uint32_t parity) {
  asm volatile("{\n.reg .pred p;\n.reg .u32 c;\nmov.u32 c, 0;\nWAIT_LOOP:\n"
               "mbarrier.try_wait.parity.shared::cta.b64 p, [%0], %1;\n@p bra WAIT_DONE;\n"
               "add.u32 c, c, 1;\nsetp.lt.u32 p, c, %2;\n@p bra WAIT_LOOP;\ntrap;\nWAIT_DONE:\n}"
               :: "r"(bar), "r"(parity), "n"(SPIN_LIMIT) : "memory");
}
__device__ __forceinline__ uint32_t mapa(uint32_t addr, uint32_t rank) { uint32_t r; asm volatile("mapa.shared::cluster.u32 %0, %1, %2;" : "=r"(r) : "r"(addr), "r"(rank)); return r; }
__device__ __forceinline__ bool elect_one() { uint32_t p; asm volatile("{\n.reg .pred P;\nelect.sync _|P, 0xffffffff;\nselp.u32 %0, 1, 0, P;\n}" : "=r"(p)); return p; }
__device__ __forceinline__ void bulk_g2s(uint32_t dst, const void* src, uint32_t bytes, uint32_t bar) {
  asm volatile("cp.async.bulk.shared::cluster.global.mbarrier::complete_tx::bytes [%0], [%1], %2, [%3];" :: "r"(dst), "l"(src), "r"(bytes), "r"(bar) : "memory");
}
__device__ __forceinline__ void bulk_s2g(void* dst, uint32_t src, uint32_t bytes) { asm volatile("cp.async.bulk.global.shared::cta.bulk_group [%0], [%1], %2;" :: "l"(dst), "r"(src), "r"(bytes) : "memory"); }
__device__ __forceinline__ void bulk_commit() { asm volatile("cp.async.bulk.commit_group;" ::: "memory"); }
template <int N> __device__ __forceinline__ void bulk_wait_read() { asm volatile("cp.async.bulk.wait_group.read %0;" :: "n"(N) : "memory"); }
template <int N> __device__ __forceinline__ void bulk_wait() { asm volatile("cp.async.bulk.wait_group %0;" :: "n"(N) : "memory"); }
__device__ __forceinline__ void tma_load(uint32_t dst, const CUtensorMap* m, int c0, int c1, uint32_t bar) {
  asm volatile("cp.async.bulk.tensor.2d.shared::cluster.global.mbarrier::complete_tx::bytes [%0], [%1, {%3, %4}], [%2];" :: "r"(dst), "l"(m), "r"(bar), "r"(c0), "r"(c1) : "memory");
}
__device__ __forceinline__ void tma_store(const CUtensorMap* m, uint32_t src, int c0, int c1) {
  asm volatile("cp.async.bulk.tensor.2d.global.shared::cta.bulk_group [%0, {%2, %3}], [%1];" :: "l"(m), "r"(src), "r"(c0), "r"(c1) : "memory");
}
__device__ __forceinline__ void prefetch_l2(const void* p, uint32_t bytes) { asm volatile("cp.async.bulk.prefetch.L2.global [%0], %1;" :: "l"(p), "r"(bytes) : "memory"); }
__device__ __forceinline__ void prefetch_map(const CUtensorMap* m) { asm volatile("prefetch.tensormap [%0];" :: "l"(m) : "memory"); }
__device__ __forceinline__ void fence_async_smem() { asm volatile("fence.proxy.async.shared::cta;" ::: "memory"); }
__device__ __forceinline__ void fence_async_global() { asm volatile("fence.proxy.async.global;" ::: "memory"); }
__device__ __forceinline__ void fence_gpu() { asm volatile("fence.acq_rel.gpu;" ::: "memory"); }
__device__ __forceinline__ void st_release(uint32_t* p, uint32_t v) { asm volatile("st.release.gpu.global.u32 [%0], %1;" :: "l"(p), "r"(v) : "memory"); }
__device__ __forceinline__ uint32_t ld_acquire(const uint32_t* p) { uint32_t v; asm volatile("ld.acquire.gpu.global.u32 %0, [%1];" : "=r"(v) : "l"(p) : "memory"); return v; }
__device__ __forceinline__ uint32_t ld_relaxed(const uint32_t* p) { uint32_t v; asm volatile("ld.relaxed.gpu.global.u32 %0, [%1];" : "=r"(v) : "l"(p) : "memory"); return v; }
__device__ __forceinline__ float2 ld_relaxed_f2(const void* p) { float2 v; asm volatile("ld.relaxed.gpu.global.v2.f32 {%0,%1}, [%2];" : "=f"(v.x), "=f"(v.y) : "l"(p) : "memory"); return v; }
__device__ __forceinline__ float4 ld_relaxed_f4(const void* p) { float4 v; asm volatile("ld.relaxed.gpu.global.v4.f32 {%0,%1,%2,%3}, [%4];" : "=f"(v.x), "=f"(v.y), "=f"(v.z), "=f"(v.w) : "l"(p) : "memory"); return v; }
__device__ __forceinline__ void st_relaxed_b64(void* p, float a, uint32_t b) {
  asm volatile("{\n.reg .b64 v;\nmov.b64 v, {%1, %2};\nst.relaxed.gpu.global.b64 [%0], v;\n}" :: "l"(p), "r"(__float_as_uint(a)), "r"(b) : "memory");
}
__device__ __forceinline__ void red_add_u32(uint32_t* p, uint32_t v) { asm volatile("red.relaxed.gpu.global.add.u32 [%0], %1;" :: "l"(p), "r"(v) : "memory"); }
__device__ __forceinline__ void red_add_f2(float* p, float a, float b) { asm volatile("red.relaxed.gpu.global.add.v2.f32 [%0], {%1, %2};" :: "l"(p), "f"(a), "f"(b) : "memory"); }
__device__ __forceinline__ void red_add_f4(float* p, float a, float b, float c, float d) { asm volatile("red.relaxed.gpu.global.add.v4.f32 [%0], {%1, %2, %3, %4};" :: "l"(p), "f"(a), "f"(b), "f"(c), "f"(d) : "memory"); }
__device__ __forceinline__ void st_async_v4(uint32_t dst, uint32_t a, uint32_t b, uint32_t c, uint32_t d, uint32_t bar) {
  asm volatile("st.async.weak.shared::cluster.mbarrier::complete_tx::bytes.v4.b32 [%0], {%1,%2,%3,%4}, [%5];" :: "r"(dst), "r"(a), "r"(b), "r"(c), "r"(d), "r"(bar) : "memory");
}
__device__ __forceinline__ void stsm4(uint32_t addr, uint32_t a, uint32_t b, uint32_t c, uint32_t d) {
  asm volatile("stmatrix.sync.aligned.m8n8.x4.shared.b16 [%0], {%1,%2,%3,%4};" :: "r"(addr), "r"(a), "r"(b), "r"(c), "r"(d) : "memory");
}
__device__ __forceinline__ void ldsm4(uint32_t addr, uint32_t& a, uint32_t& b, uint32_t& c, uint32_t& d) {
  asm volatile("ldmatrix.sync.aligned.m8n8.x4.shared.b16 {%0,%1,%2,%3}, [%4];" : "=r"(a), "=r"(b), "=r"(c), "=r"(d) : "r"(addr) : "memory");
}
__device__ __forceinline__ void ldsm4t(uint32_t addr, uint32_t& a, uint32_t& b, uint32_t& c, uint32_t& d) {
  asm volatile("ldmatrix.sync.aligned.m8n8.x4.trans.shared.b16 {%0,%1,%2,%3}, [%4];" : "=r"(a), "=r"(b), "=r"(c), "=r"(d) : "r"(addr) : "memory");
}
__device__ __forceinline__ float2 lds_f2(uint32_t addr) { float2 v; asm volatile("ld.shared.v2.f32 {%0,%1}, [%2];" : "=f"(v.x), "=f"(v.y) : "r"(addr) : "memory"); return v; }
__device__ __forceinline__ uint32_t lds_u32(uint32_t addr) { uint32_t v; asm volatile("ld.shared.u32 %0, [%1];" : "=r"(v) : "r"(addr) : "memory"); return v; }
__device__ __forceinline__ void sts_u4(uint32_t addr, uint4 v) { asm volatile("st.shared.v4.u32 [%0], {%1,%2,%3,%4};" :: "r"(addr), "r"(v.x), "r"(v.y), "r"(v.z), "r"(v.w) : "memory"); }
__device__ __forceinline__ uint4 ld_relaxed_u4(const void* p) { uint4 v; asm volatile("ld.relaxed.gpu.global.v4.u32 {%0,%1,%2,%3}, [%4];" : "=r"(v.x), "=r"(v.y), "=r"(v.z), "=r"(v.w) : "l"(p) : "memory"); return v; }
__device__ __forceinline__ void st_relaxed_u4(void* p, uint4 v) { asm volatile("st.relaxed.gpu.global.v4.u32 [%0], {%1,%2,%3,%4};" :: "l"(p), "r"(v.x), "r"(v.y), "r"(v.z), "r"(v.w) : "memory"); }
__device__ __forceinline__ void st_relaxed_u32(uint32_t* p, uint32_t v) { asm volatile("st.relaxed.gpu.global.u32 [%0], %1;" :: "l"(p), "r"(v) : "memory"); }
__device__ __forceinline__ void st_relaxed_f4(void* p, float a, float b, float c, uint32_t d) { asm volatile("st.relaxed.gpu.global.v4.b32 [%0], {%1,%2,%3,%4};" :: "l"(p), "r"(__float_as_uint(a)), "r"(__float_as_uint(b)), "r"(__float_as_uint(c)), "r"(d) : "memory"); }
__device__ __forceinline__ uint2 lds_u2(uint32_t addr) { uint2 v; asm volatile("ld.shared.v2.u32 {%0,%1}, [%2];" : "=r"(v.x), "=r"(v.y) : "r"(addr) : "memory"); return v; }
__device__ __forceinline__ uint4 lds_u4(uint32_t addr) { uint4 v; asm volatile("ld.shared.v4.u32 {%0,%1,%2,%3}, [%4];" : "=r"(v.x), "=r"(v.y), "=r"(v.z), "=r"(v.w) : "r"(addr) : "memory"); return v; }
__device__ __forceinline__ void sts_f2(uint32_t addr, float a, float b) { asm volatile("st.shared.v2.f32 [%0], {%1,%2};" :: "r"(addr), "f"(a), "f"(b) : "memory"); }
__device__ __forceinline__ void sts_u2(uint32_t addr, uint32_t a, uint32_t b) { asm volatile("st.shared.v2.u32 [%0], {%1,%2};" :: "r"(addr), "r"(a), "r"(b) : "memory"); }
__device__ __forceinline__ void sts_f4(uint32_t addr, float4 v) { asm volatile("st.shared.v4.f32 [%0], {%1,%2,%3,%4};" :: "r"(addr), "f"(v.x), "f"(v.y), "f"(v.z), "f"(v.w) : "memory"); }
__device__ __forceinline__ void mma16816(float (&c)[4], uint32_t a0, uint32_t a1, uint32_t a2, uint32_t a3, uint32_t b0, uint32_t b1) {
  asm volatile("mma.sync.aligned.m16n8k16.row.col.f32.bf16.bf16.f32 {%0,%1,%2,%3}, {%4,%5,%6,%7}, {%8,%9}, {%0,%1,%2,%3};"
               : "+f"(c[0]), "+f"(c[1]), "+f"(c[2]), "+f"(c[3]) : "r"(a0), "r"(a1), "r"(a2), "r"(a3), "r"(b0), "r"(b1));
}
__device__ __forceinline__ uint32_t pack_bf16(float lo, float hi) { uint32_t r; asm("cvt.rn.bf16x2.f32 %0, %1, %2;" : "=r"(r) : "f"(hi), "f"(lo)); return r; }
__device__ __forceinline__ uint32_t pack_bf16_relu(float lo, float hi) { uint32_t r; asm("cvt.rn.relu.bf16x2.f32 %0, %1, %2;" : "=r"(r) : "f"(hi), "f"(lo)); return r; }
__device__ __forceinline__ float bf_lo(uint32_t v) { return __uint_as_float(v << 16); }
__device__ __forceinline__ float bf_hi(uint32_t v) { return __uint_as_float(v & 0xffff0000u); }
__device__ __forceinline__ float ex2(float x) { float y; asm("ex2.approx.ftz.f32 %0, %1;" : "=f"(y) : "f"(x)); return y; }
__device__ __forceinline__ float rcp(float x) { float y; asm("rcp.approx.ftz.f32 %0, %1;" : "=f"(y) : "f"(x)); return y; }
__device__ __forceinline__ float phi_y(float y) { return fmaf(fmaxf(y, 1.4426950408889634e-6f), 0.6931471805599453f, ex2(fminf(y, 0.f))); }
__device__ __forceinline__ int opaque(int x) { int y; asm volatile("mov.u32 %0, %1;" : "=r"(y) : "r"(x)); return y; }
__device__ __forceinline__ void wg_fence() { asm volatile("wgmma.fence.sync.aligned;" ::: "memory"); }
__device__ __forceinline__ void wg_fence_in() { if (!NOFENCE) wg_fence(); }
__device__ __forceinline__ void wg_commit() { asm volatile("wgmma.commit_group.sync.aligned;" ::: "memory"); }
template <int N> __device__ __forceinline__ void wg_wait() { asm volatile("wgmma.wait_group.sync.aligned %0;" :: "n"(N) : "memory"); }
template <int N> __device__ __forceinline__ void fence_regs(float (&d)[N]) {
#pragma unroll
  for (int i = 0; i < N; i++) asm volatile("" : "+f"(d[i]) :: "memory");
}
template <int N> __device__ __forceinline__ void zero_regs(float (&d)[N]) {
#pragma unroll
  for (int i = 0; i < N; i++) d[i] = 0.f;
  fence_regs(d);
}
__device__ __forceinline__ void wg_bar(int wg) { if (wg == 0) asm volatile("bar.sync 1, 128;" ::: "memory"); else asm volatile("bar.sync 2, 128;" ::: "memory"); }
__device__ __forceinline__ uint32_t desc_lo(uint32_t addr, uint32_t lbo) { return ((addr & 0x3FFFF) >> 4) | ((lbo >> 4) << 16); }
constexpr uint32_t HI_SW = 0x40000040u;
constexpr uint32_t HI_NS = 0x00000008u;
template <int I> struct IC { static constexpr int value = I; };
template <int B, int E, class F> __device__ __forceinline__ void static_for(F&& f) {
  if constexpr (B < E) { f(IC<B>{}); static_for<B + 1, E>(f); }
}

template <int OA, int OB, uint32_t HA>
__device__ __forceinline__ void wgmma_n64_init(float (&d)[32], uint32_t la, uint32_t lb) {
  asm volatile("{\n.reg .pred p;\n.reg .b32 ta, tb;\n.reg .b64 da, db;\n"
    "setp.ne.b32 p, 0, 0;\nadd.u32 ta, %32, %34;\nadd.u32 tb, %33, %35;\n"
    "mov.b64 da, {ta, %36};\nmov.b64 db, {tb, 0x40000040};\n"
    "wgmma.mma_async.sync.aligned.m64n64k16.f32.bf16.bf16 "
    "{%0, %1, %2, %3, %4, %5, %6, %7, %8, %9, %10, %11, %12, %13, %14, %15, "
    "%16, %17, %18, %19, %20, %21, %22, %23, %24, %25, %26, %27, %28, %29, %30, %31}, "
    "da, db, p, 1, 1, 0, 1;\n}"
    : "=f"(d[0]), "=f"(d[1]), "=f"(d[2]), "=f"(d[3]), "=f"(d[4]), "=f"(d[5]), "=f"(d[6]), "=f"(d[7]),
      "=f"(d[8]), "=f"(d[9]), "=f"(d[10]), "=f"(d[11]), "=f"(d[12]), "=f"(d[13]), "=f"(d[14]), "=f"(d[15]),
      "=f"(d[16]), "=f"(d[17]), "=f"(d[18]), "=f"(d[19]), "=f"(d[20]), "=f"(d[21]), "=f"(d[22]), "=f"(d[23]),
      "=f"(d[24]), "=f"(d[25]), "=f"(d[26]), "=f"(d[27]), "=f"(d[28]), "=f"(d[29]), "=f"(d[30]), "=f"(d[31])
    : "r"(la), "r"(lb), "n"(OA), "n"(OB), "n"(HA));
}
template <int OA, int OB, uint32_t HA>
__device__ __forceinline__ void wgmma_n128_init(float (&d)[32], float (&e)[32], uint32_t la, uint32_t lb) {
  asm volatile("{\n.reg .pred p;\n.reg .b32 ta, tb;\n.reg .b64 da, db;\n"
    "setp.ne.b32 p, 0, 0;\nadd.u32 ta, %64, %66;\nadd.u32 tb, %65, %67;\n"
    "mov.b64 da, {ta, %68};\nmov.b64 db, {tb, 0x40000040};\n"
    "wgmma.mma_async.sync.aligned.m64n128k16.f32.bf16.bf16 "
    "{%0, %1, %2, %3, %4, %5, %6, %7, %8, %9, %10, %11, %12, %13, %14, %15, "
    "%16, %17, %18, %19, %20, %21, %22, %23, %24, %25, %26, %27, %28, %29, %30, %31, "
    "%32, %33, %34, %35, %36, %37, %38, %39, %40, %41, %42, %43, %44, %45, %46, %47, "
    "%48, %49, %50, %51, %52, %53, %54, %55, %56, %57, %58, %59, %60, %61, %62, %63}, "
    "da, db, p, 1, 1, 0, 1;\n}"
    : "=f"(d[0]), "=f"(d[1]), "=f"(d[2]), "=f"(d[3]), "=f"(d[4]), "=f"(d[5]), "=f"(d[6]), "=f"(d[7]),
      "=f"(d[8]), "=f"(d[9]), "=f"(d[10]), "=f"(d[11]), "=f"(d[12]), "=f"(d[13]), "=f"(d[14]), "=f"(d[15]),
      "=f"(d[16]), "=f"(d[17]), "=f"(d[18]), "=f"(d[19]), "=f"(d[20]), "=f"(d[21]), "=f"(d[22]), "=f"(d[23]),
      "=f"(d[24]), "=f"(d[25]), "=f"(d[26]), "=f"(d[27]), "=f"(d[28]), "=f"(d[29]), "=f"(d[30]), "=f"(d[31]),
      "=f"(e[0]), "=f"(e[1]), "=f"(e[2]), "=f"(e[3]), "=f"(e[4]), "=f"(e[5]), "=f"(e[6]), "=f"(e[7]),
      "=f"(e[8]), "=f"(e[9]), "=f"(e[10]), "=f"(e[11]), "=f"(e[12]), "=f"(e[13]), "=f"(e[14]), "=f"(e[15]),
      "=f"(e[16]), "=f"(e[17]), "=f"(e[18]), "=f"(e[19]), "=f"(e[20]), "=f"(e[21]), "=f"(e[22]), "=f"(e[23]),
      "=f"(e[24]), "=f"(e[25]), "=f"(e[26]), "=f"(e[27]), "=f"(e[28]), "=f"(e[29]), "=f"(e[30]), "=f"(e[31])
    : "r"(la), "r"(lb), "n"(OA), "n"(OB), "n"(HA));
}
template <int OA, int OB, uint32_t HA>
__device__ __forceinline__ void wgmma_n48_init(float (&d)[24], uint32_t la, uint32_t lb) {
  asm volatile("{\n.reg .pred p;\n.reg .b32 ta, tb;\n.reg .b64 da, db;\n"
    "setp.ne.b32 p, 0, 0;\nadd.u32 ta, %24, %26;\nadd.u32 tb, %25, %27;\n"
    "mov.b64 da, {ta, %28};\nmov.b64 db, {tb, 0x40000040};\n"
    "wgmma.mma_async.sync.aligned.m64n48k16.f32.bf16.bf16 "
    "{%0, %1, %2, %3, %4, %5, %6, %7, %8, %9, %10, %11, %12, %13, %14, %15, "
    "%16, %17, %18, %19, %20, %21, %22, %23}, "
    "da, db, p, 1, 1, 0, 1;\n}"
    : "=f"(d[0]), "=f"(d[1]), "=f"(d[2]), "=f"(d[3]), "=f"(d[4]), "=f"(d[5]), "=f"(d[6]), "=f"(d[7]),
      "=f"(d[8]), "=f"(d[9]), "=f"(d[10]), "=f"(d[11]), "=f"(d[12]), "=f"(d[13]), "=f"(d[14]), "=f"(d[15]),
      "=f"(d[16]), "=f"(d[17]), "=f"(d[18]), "=f"(d[19]), "=f"(d[20]), "=f"(d[21]), "=f"(d[22]), "=f"(d[23])
    : "r"(la), "r"(lb), "n"(OA), "n"(OB), "n"(HA));
}
template <int OA, int OB, uint32_t HA>
__device__ __forceinline__ void wgmma_n64(float (&d)[32], uint32_t la, uint32_t lb) {
  asm volatile("{\n.reg .pred p;\n.reg .b32 ta, tb;\n.reg .b64 da, db;\n"
    "setp.eq.b32 p, 0, 0;\nadd.u32 ta, %32, %34;\nadd.u32 tb, %33, %35;\n"
    "mov.b64 da, {ta, %36};\nmov.b64 db, {tb, 0x40000040};\n"
    "wgmma.mma_async.sync.aligned.m64n64k16.f32.bf16.bf16 "
    "{%0, %1, %2, %3, %4, %5, %6, %7, %8, %9, %10, %11, %12, %13, %14, %15, "
    "%16, %17, %18, %19, %20, %21, %22, %23, %24, %25, %26, %27, %28, %29, %30, %31}, "
    "da, db, p, 1, 1, 0, 1;\n}"
    : "+f"(d[0]), "+f"(d[1]), "+f"(d[2]), "+f"(d[3]), "+f"(d[4]), "+f"(d[5]), "+f"(d[6]), "+f"(d[7]),
      "+f"(d[8]), "+f"(d[9]), "+f"(d[10]), "+f"(d[11]), "+f"(d[12]), "+f"(d[13]), "+f"(d[14]), "+f"(d[15]),
      "+f"(d[16]), "+f"(d[17]), "+f"(d[18]), "+f"(d[19]), "+f"(d[20]), "+f"(d[21]), "+f"(d[22]), "+f"(d[23]),
      "+f"(d[24]), "+f"(d[25]), "+f"(d[26]), "+f"(d[27]), "+f"(d[28]), "+f"(d[29]), "+f"(d[30]), "+f"(d[31])
    : "r"(la), "r"(lb), "n"(OA), "n"(OB), "n"(HA));
}
template <int OA, int OB, uint32_t HA>
__device__ __forceinline__ void wgmma_n128(float (&d)[32], float (&e)[32], uint32_t la, uint32_t lb) {
  asm volatile("{\n.reg .pred p;\n.reg .b32 ta, tb;\n.reg .b64 da, db;\n"
    "setp.eq.b32 p, 0, 0;\nadd.u32 ta, %64, %66;\nadd.u32 tb, %65, %67;\n"
    "mov.b64 da, {ta, %68};\nmov.b64 db, {tb, 0x40000040};\n"
    "wgmma.mma_async.sync.aligned.m64n128k16.f32.bf16.bf16 "
    "{%0, %1, %2, %3, %4, %5, %6, %7, %8, %9, %10, %11, %12, %13, %14, %15, "
    "%16, %17, %18, %19, %20, %21, %22, %23, %24, %25, %26, %27, %28, %29, %30, %31, "
    "%32, %33, %34, %35, %36, %37, %38, %39, %40, %41, %42, %43, %44, %45, %46, %47, "
    "%48, %49, %50, %51, %52, %53, %54, %55, %56, %57, %58, %59, %60, %61, %62, %63}, "
    "da, db, p, 1, 1, 0, 1;\n}"
    : "+f"(d[0]), "+f"(d[1]), "+f"(d[2]), "+f"(d[3]), "+f"(d[4]), "+f"(d[5]), "+f"(d[6]), "+f"(d[7]),
      "+f"(d[8]), "+f"(d[9]), "+f"(d[10]), "+f"(d[11]), "+f"(d[12]), "+f"(d[13]), "+f"(d[14]), "+f"(d[15]),
      "+f"(d[16]), "+f"(d[17]), "+f"(d[18]), "+f"(d[19]), "+f"(d[20]), "+f"(d[21]), "+f"(d[22]), "+f"(d[23]),
      "+f"(d[24]), "+f"(d[25]), "+f"(d[26]), "+f"(d[27]), "+f"(d[28]), "+f"(d[29]), "+f"(d[30]), "+f"(d[31]),
      "+f"(e[0]), "+f"(e[1]), "+f"(e[2]), "+f"(e[3]), "+f"(e[4]), "+f"(e[5]), "+f"(e[6]), "+f"(e[7]),
      "+f"(e[8]), "+f"(e[9]), "+f"(e[10]), "+f"(e[11]), "+f"(e[12]), "+f"(e[13]), "+f"(e[14]), "+f"(e[15]),
      "+f"(e[16]), "+f"(e[17]), "+f"(e[18]), "+f"(e[19]), "+f"(e[20]), "+f"(e[21]), "+f"(e[22]), "+f"(e[23]),
      "+f"(e[24]), "+f"(e[25]), "+f"(e[26]), "+f"(e[27]), "+f"(e[28]), "+f"(e[29]), "+f"(e[30]), "+f"(e[31])
    : "r"(la), "r"(lb), "n"(OA), "n"(OB), "n"(HA));
}
template <int OA, int OB, uint32_t HA>
__device__ __forceinline__ void wgmma_n48(float (&d)[24], uint32_t la, uint32_t lb) {
  asm volatile("{\n.reg .pred p;\n.reg .b32 ta, tb;\n.reg .b64 da, db;\n"
    "setp.eq.b32 p, 0, 0;\nadd.u32 ta, %24, %26;\nadd.u32 tb, %25, %27;\n"
    "mov.b64 da, {ta, %28};\nmov.b64 db, {tb, 0x40000040};\n"
    "wgmma.mma_async.sync.aligned.m64n48k16.f32.bf16.bf16 "
    "{%0, %1, %2, %3, %4, %5, %6, %7, %8, %9, %10, %11, %12, %13, %14, %15, "
    "%16, %17, %18, %19, %20, %21, %22, %23}, "
    "da, db, p, 1, 1, 0, 1;\n}"
    : "+f"(d[0]), "+f"(d[1]), "+f"(d[2]), "+f"(d[3]), "+f"(d[4]), "+f"(d[5]), "+f"(d[6]), "+f"(d[7]),
      "+f"(d[8]), "+f"(d[9]), "+f"(d[10]), "+f"(d[11]), "+f"(d[12]), "+f"(d[13]), "+f"(d[14]), "+f"(d[15]),
      "+f"(d[16]), "+f"(d[17]), "+f"(d[18]), "+f"(d[19]), "+f"(d[20]), "+f"(d[21]), "+f"(d[22]), "+f"(d[23])
    : "r"(la), "r"(lb), "n"(OA), "n"(OB), "n"(HA));
}

__device__ __forceinline__ void publish_stats(const uint32_t (&xr)[16], float2* dst  , int t, uint32_t tag) {
  float s0 = 0.f, s1 = 0.f;
#pragma unroll
  for (int j = 0; j < 8; j++) { s0 += bf_lo(xr[2 * j]) + bf_hi(xr[2 * j]); s1 += bf_lo(xr[2 * j + 1]) + bf_hi(xr[2 * j + 1]); }
  s0 += __shfl_xor_sync(0xffffffff, s0, 1); s1 += __shfl_xor_sync(0xffffffff, s1, 1);
  s0 += __shfl_xor_sync(0xffffffff, s0, 2); s1 += __shfl_xor_sync(0xffffffff, s1, 2);
  const float m0 = s0 * (1.f / 64.f), m1 = s1 * (1.f / 64.f);
  float q0 = 0.f, q1 = 0.f;
#pragma unroll
  for (int j = 0; j < 8; j++) {
    float a = bf_lo(xr[2 * j]) - m0, b = bf_hi(xr[2 * j]) - m0, c = bf_lo(xr[2 * j + 1]) - m1, d = bf_hi(xr[2 * j + 1]) - m1;
    q0 = fmaf(a, a, q0); q0 = fmaf(b, b, q0); q1 = fmaf(c, c, q1); q1 = fmaf(d, d, q1);
  }
  q0 += __shfl_xor_sync(0xffffffff, q0, 1); q1 += __shfl_xor_sync(0xffffffff, q1, 1);
  q0 += __shfl_xor_sync(0xffffffff, q0, 2); q1 += __shfl_xor_sync(0xffffffff, q1, 2);
  if (t < 2) st_relaxed_b64(dst + 8 * t, t ? s1 : s0, (__float_as_uint(t ? q1 : q0) & ~1u) | tag);
}

__device__ __forceinline__ void gather_stats(const float2* src  , uint32_t sm_dst, uint32_t bar, int lane, uint32_t tag) {
  const float2* p = src + lane * 2;
  float4 v[8];
  uint32_t cnt = 0;
  while (true) {
#pragma unroll
    for (int i = 0; i < 8; i++) v[i] = ld_relaxed_f4(p + i * 64);
    uint32_t bad = 0;
#pragma unroll
    for (int i = 0; i < 8; i++) bad |= (__float_as_uint(v[i].y) ^ tag) | (__float_as_uint(v[i].w) ^ tag);
    if (__all_sync(0xffffffff, (bad & 1u) == 0)) break;
    if (++cnt > SPIN_LIMIT) __trap();
    __nanosleep(100);
  }
  float sa = 0.f, sb = 0.f, qa = 0.f, qb = 0.f;
#pragma unroll
  for (int i = 0; i < 8; i++) { sa += v[i].x; qa += v[i].y; sb += v[i].z; qb += v[i].w; }
  const float ma = sa * (1.f / 512.f), mb = sb * (1.f / 512.f);
  float da = 0.f, db = 0.f;
#pragma unroll
  for (int i = 0; i < 8; i++) {
    const float a = v[i].x * (1.f / 64.f) - ma, b = v[i].z * (1.f / 64.f) - mb;
    da = fmaf(a, a, da); db = fmaf(b, b, db);
  }
  sts_f4(sm_dst + lane * 16, make_float4(rsqrtf(fmaf(da, 64.f, qa) * (1.f / 512.f) + 1e-5f), -ma, rsqrtf(fmaf(db, 64.f, qb) * (1.f / 512.f) + 1e-5f), -mb));
  __syncwarp();
  if (lane == 0) mbar_arrive(bar);
}

__device__ __forceinline__ void colsum_task(const __nv_bfloat16* p  , int pitch, bool ok, int row0, float4* dst  , int lane, uint32_t tag) {
  const int rg = lane >> 3;
  float a[8];
#pragma unroll
  for (int i = 0; i < 8; i++) a[i] = 0.f;
  if (ok) {
    uint4 v[8];
#pragma unroll
    for (int i = 0; i < 8; i++) v[i] = __ldg((const uint4*)(p + (size_t)(row0 + 4 * i + rg) * pitch));
#pragma unroll
    for (int i = 0; i < 8; i++) {
      a[0] += bf_lo(v[i].x); a[1] += bf_hi(v[i].x); a[2] += bf_lo(v[i].y); a[3] += bf_hi(v[i].y);
      a[4] += bf_lo(v[i].z); a[5] += bf_hi(v[i].z); a[6] += bf_lo(v[i].w); a[7] += bf_hi(v[i].w);
    }
  }
#pragma unroll
  for (int i = 0; i < 8; i++) { a[i] += __shfl_xor_sync(0xffffffff, a[i], 8); a[i] += __shfl_xor_sync(0xffffffff, a[i], 16); }
  if (rg == 0) {
    st_relaxed_f4(dst, a[0], a[1], a[2], (__float_as_uint(a[3]) & ~1u) | tag);
    st_relaxed_f4(dst + 1, a[4], a[5], a[6], (__float_as_uint(a[7]) & ~1u) | tag);
  }
}
__device__ __forceinline__ void colsum_gather(const float4* src, uint32_t sm_dst, int nunits, int lane, uint32_t tag) {
#pragma unroll 1
  for (int j = 0; j < 3; j++) {
    const float4* p = src + (lane >> 4) * 8 * 48 + j * 16 + (lane & 15);
    float4 v[8];
    uint32_t cnt = 0;
    while (true) {
      uint32_t bad = 0;
#pragma unroll
      for (int i = 0; i < 8; i++) v[i] = ld_relaxed_f4(p + i * 48);
#pragma unroll
      for (int i = 0; i < 8; i++) bad |= __float_as_uint(v[i].w) ^ tag;
      if (__all_sync(0xffffffff, (bad & 1u) == 0)) break;
      if (++cnt > SPIN_LIMIT) __trap();
    }
    float4 a = v[0];
#pragma unroll
    for (int i = 1; i < 8; i++) { a.x += v[i].x; a.y += v[i].y; a.z += v[i].z; a.w += v[i].w; }
    a.x += __shfl_xor_sync(0xffffffff, a.x, 16); a.y += __shfl_xor_sync(0xffffffff, a.y, 16);
    a.z += __shfl_xor_sync(0xffffffff, a.z, 16); a.w += __shfl_xor_sync(0xffffffff, a.w, 16);
    if (lane < 16 && j * 16 + lane < nunits) sts_f4(sm_dst + (j * 16 + lane) * 16, a);
  }
  __syncwarp();
}

__device__ __forceinline__ void wait_flag_acq(const uint32_t* f, uint32_t ev) {
  uint32_t cnt = 0;
  while ((int32_t)(ld_acquire(f) - ev) < 0) { if (++cnt > SPIN_LIMIT) __trap(); }
}
__device__ __forceinline__ void wait_flags(const uint32_t* f  , uint32_t ev) {
  uint32_t cnt = 0;
  while (!__all_sync(0xffffffff, (int32_t)(ld_relaxed(f) - ev) >= 0)) { if (++cnt > SPIN_LIMIT) __trap(); }
}
__device__ __forceinline__ void set_flags(uint4* flag  , uint32_t ev, int lane) {
  if (lane < 16) asm volatile("st.relaxed.gpu.global.v4.u32 [%0], {%1,%1,%1,%1};" :: "l"(flag + (lane >> 1) * 64 + (lane & 1)), "r"(ev) : "memory");
}
__device__ __forceinline__ void order_before(int h) {
}
__device__ __forceinline__ void order_after(int h) {
}
__device__ __forceinline__ void fetch_chunks(const uint4* gbuf  , const uint4* flags, uint32_t abase, uint32_t afull, int r, uint32_t ev, int lane) {
  const uint32_t* f = (const uint32_t*)(flags + r * 64 + ((r + (lane >> 2)) & 7) * 8 + (lane & 3) * 2);
  uint32_t todo = 0xff & ~((2u << NLL) - 1), cnt = 0;
  while (todo) {
    const uint32_t rdy = __ballot_sync(0xffffffff, (int32_t)(ld_relaxed(f) - ev) >= 0);
#pragma unroll
    for (int i = NLL + 1; i < 8; i++) {
      if (((todo >> i) & 1) && ((rdy >> (4 * i)) & 15) == 15) {
        if (elect_one()) {
          mbar_expect_tx(afull + i * 8, 8192);
          bulk_g2s(abase + i * 8192, gbuf + ((r + i) & 7) * 512, 8192, afull + i * 8);
        }
        todo &= ~(1u << i);
      }
    }
    if (++cnt > SPIN_LIMIT) __trap();
  }
  __syncwarp();
}

__global__ void __cluster_dims__(2, 1, 1) __launch_bounds__(384, 1)
fused_kernel(const __grid_constant__ CUtensorMap tm_x, const __grid_constant__ CUtensorMap tm_out,
             const __grid_constant__ CUtensorMap tm_wqkv, const __grid_constant__ CUtensorMap tm_wo,
             const __grid_constant__ CUtensorMap tm_w1, const __grid_constant__ CUtensorMap tm_w2, const __grid_constant__ CUtensorMap tm_w2s,
             const __nv_bfloat16* __restrict__ wqkv, const __nv_bfloat16* __restrict__ wo,
             const __nv_bfloat16* __restrict__ w1, const __nv_bfloat16* __restrict__ w2) {
  extern __shared__ __align__(1024) uint8_t smem_raw[];
  const uint32_t sb = smem_u32(smem_raw);
  const int warp = __shfl_sync(0xffffffff, threadIdx.x >> 5, 0);
  const int bid = __shfl_sync(0xffffffff, opaque(blockIdx.x), 0);
  int cb, r;
  {
    const int cl = bid >> 1;
    cb = cl >> 2; r = (cl & 3) * 2 + (bid & 1);
  }

  const int prof_id = cb * 8 + r; (void)prof_id;
  if (threadIdx.x == 0) {
    if (sb & 1023) __trap();
    for (int i = 0; i < 4; i++) { mbar_init(sb + B_BFULL + i * 8, 1); mbar_init(sb + B_BEMPTY + i * 8, 8); }
    for (int i = 0; i < 16; i++) mbar_init(sb + B_AFULL + i * 8, 1);
    for (int i = 0; i < 6; i++) { mbar_init(sb + B_AFREE + i * 8, 4); mbar_init(sb + B_OWN + i * 8, 4); }
    for (int i = 0; i < 2; i++) { mbar_init(sb + B_STAT + i * 8, 1); mbar_init(sb + B_PRDY + i * 8, 1); mbar_init(sb + B_PFREE + i * 8, 4); }
    mbar_init(sb + B_CSRDY, 1); mbar_init(sb + B_CSRDY + 8, 1); mbar_init(sb + B_KVDONE, 4); mbar_init(sb + B_KVRDY, 1);
    asm volatile("fence.mbarrier_init.release.cluster;" ::: "memory");
  }
  __syncthreads();
  asm volatile("barrier.cluster.arrive.relaxed.aligned;" ::: "memory");

  if (warp >= 8) {
  asm volatile("setmaxnreg.dec.sync.aligned.u32 96;");
  const int lane = __shfl_sync(0xffffffff, threadIdx.x & 31, threadIdx.x & 31);
  const uint32_t epoch = ld_relaxed(g_epoch + bid * 8);
  if (warp == 8) {
    uint32_t st = 0;
    auto acquire = [&](uint32_t bytes) -> uint32_t {
      const uint32_t s = st & 3;
      mbar_wait(sb + B_BEMPTY + s * 8, ((st >> 2) & 1) ^ 1);
      st++;
      return s;
    };
    if (lane == 0) { prefetch_map(&tm_wqkv); prefetch_map(&tm_wo); prefetch_map(&tm_w1); prefetch_map(&tm_w2); prefetch_map(&tm_w2s); }
#pragma unroll 1
    for (int l = 0; l < 2; l++) {
#pragma unroll 1
      for (int i = 0; i < 8; i++) {
        const uint32_t s = acquire(0), dst = sb + SM_RING + s * SLOT, fb = sb + B_BFULL + s * 8;
        const int kc = (r + i) & 7;
        if (elect_one()) { mbar_expect_tx(fb, 16384); tma_load(dst, &tm_wqkv, 512 + 64 * r, 64 * kc, fb); tma_load(dst + 8192, &tm_wqkv, 1024 + 64 * r, 64 * kc, fb); }
      }
#pragma unroll 1
      for (int i = 0; i < 4; i++) {
        const uint32_t s = acquire(0), dst = sb + SM_RING + s * SLOT, fb = sb + B_BFULL + s * 8;
        if (elect_one()) { mbar_expect_tx(fb, 16384); tma_load(dst, &tm_wqkv, 64 * r, 64 * ((r + 2 * i) & 7), fb); tma_load(dst + 8192, &tm_wqkv, 64 * r, 64 * ((r + 2 * i + 1) & 7), fb); }
      }
#pragma unroll 1
      for (int i = 0; i < 4; i++) {
        const uint32_t s = acquire(0), dst = sb + SM_RING + s * SLOT, fb = sb + B_BFULL + s * 8;
        if (elect_one()) { mbar_expect_tx(fb, 16384); tma_load(dst, &tm_wo, 64 * r, 64 * ((r + 2 * i) & 7), fb); tma_load(dst + 8192, &tm_wo, 64 * r, 64 * ((r + 2 * i + 1) & 7), fb); }
      }
#pragma unroll 1
      for (int i = 0; i < 8; i++) {
        const uint32_t s = acquire(0), dst = sb + SM_RING + s * SLOT, fb = sb + B_BFULL + s * 8;
        const int kc = (r + i) & 7;
        if (elect_one()) { mbar_expect_tx(fb, 16384); tma_load(dst, &tm_w1, kHS * r, 64 * kc, fb); tma_load(dst + 8192, &tm_w1, kHS * r + 64, 64 * kc, fb); }
      }
#pragma unroll 1
      for (int i = 0; i < 4; i++) {
        const uint32_t s = acquire(0), dst = sb + SM_RING + s * SLOT, fb = sb + B_BFULL + s * 8;
        if (elect_one()) { mbar_expect_tx(fb, 16384); tma_load(dst, &tm_w1, kHS * r + 128, 64 * ((r + 2 * i) & 7), fb); tma_load(dst + 8192, &tm_w1, kHS * r + 128, 64 * ((r + 2 * i + 1) & 7), fb); }
      }
#pragma unroll 1
      for (int i = 0; i < 12; i++) {
        const uint32_t s = acquire(0), dst = sb + SM_RING + s * SLOT, fb = sb + B_BFULL + s * 8;
        const int t = i < 3 ? 0 : i < 9 ? (i - 1) >> 1 : i - 8, bb = i < 3 ? i : i < 9 ? (i - 1) & 1 : 2;
        const int row = kHS * ((r + 2 * t) & 7) + 64 * bb;
        if (elect_one()) {
          const CUtensorMap* m = bb == 2 ? &tm_w2s : &tm_w2;
          mbar_expect_tx(fb, bb == 2 ? 12288 : 16384); tma_load(dst, m, 64 * (r ^ 1), row, fb); tma_load(dst + 8192, m, 64 * r, row, fb);
        }
      }
    }
    asm volatile("barrier.cluster.wait.aligned;" ::: "memory");
  } else if (warp == 9 || warp == 10) {
    const int h = warp - 9, half0 = cb * 2 + h;
    if (elect_one()) {
      const uint32_t abase = sb + h * 65536, afull = sb + B_AFULL + h * 64;
      prefetch_map(&tm_x);
      for (int i = 0; i < 8; i++) { mbar_expect_tx(afull + i * 8, 8192); tma_load(abase + i * 8192, &tm_x, 64 * ((r + i) & 7), 128 * cb + 64 * h, afull + i * 8); }
    }
    __syncwarp();
    const uint32_t ev0 = epoch * 16, tag = (epoch + 1) & 1;
    for (int u = 0; u < 4; u++) set_flags(g_flags + half0 * 512 + r * 8 + u * 2, ev0, lane);
    colsum_task(wqkv + (1 + h) * 512 + 64 * r + 8 * (lane & 7), 3 * kD, true, 32 * cb, g_cs + ((r * 2 + 0) * 16 + cb) * 48 + (1 + h) * 16 + 2 * (lane & 7), lane, tag);
    gather_stats(g_stats + (0 * 32 + half0) * 512, sb + SM_STAT + h * 512, sb + B_STAT + h * 8, lane, tag);
#pragma unroll 1
    for (int b = h; b < 3; b += 2) {
      const int col = 64 * b + 8 * (lane & 7);
      colsum_task(w1 + kHS * r + col, kFF, col < kHS && kHS * r + col < kFF, 32 * cb, g_cs + ((r * 2 + 1) * 16 + cb) * 48 + b * 16 + 2 * (lane & 7), lane, tag);
    }
    asm volatile("barrier.cluster.wait.aligned;" ::: "memory");
    uint32_t p0 = 0;
#pragma unroll 1
    for (int l = 0; l < 2; l++) {
      const uint32_t ev = ev0 + l * 6;
      const int half = opaque(half0);
      const uint32_t abase = sb + h * 65536, afull = sb + B_AFULL + h * 64, afree = sb + B_AFREE + h * 24, own = sb + B_OWN + h * 24;
      uint4* flags = g_flags + half * 512;
      mbar_wait(afree, p0); p0 ^= 1;
      STAMP(2 + h, l * 16 + 0);
      fetch_chunks(g_act + (0 * 32 + half) * 4096, flags, abase, afull, r, ev + 1, lane);
      STAMP(2 + h, l * 16 + 1);
      mbar_wait(afree, p0); p0 ^= 1;
      STAMP(2 + h, l * 16 + 2);
      fetch_chunks(g_act + (1 * 32 + half) * 4096, flags, abase, afull, r, ev + 2, lane);
      STAMP(2 + h, l * 16 + 4);
      gather_stats(g_stats + ((2 * l + 1) * 32 + half) * 512, sb + SM_STAT + h * 512, sb + B_STAT + h * 8, lane, tag);
      STAMP(2 + h, l * 16 + 3);
      uint4* hb = g_h + half * 8 * 1536;
      const uint32_t* hf = (const uint32_t*)(flags + r * 64 + ((r + 2 + 2 * (lane & 3)) & 7) * 8);
      auto fetch_h = [&](int t, int bb, int slot) {
        if (elect_one()) {
          const uint32_t bytes = bb == 2 ? 6144 : 8192;
          mbar_expect_tx(afull + slot * 8, bytes);
          bulk_g2s(abase + slot * 8192, hb + ((r + 2 * t) & 7) * 1536 + bb * 512, bytes, afull + slot * 8);
        }
      };
      auto wait_h = [&](uint32_t mask, uint32_t e) {
        uint32_t cnt = 0;
        while ((__ballot_sync(0xffffffff, (int32_t)(ld_relaxed(hf) - e) >= 0) & mask) != mask) { if (++cnt > SPIN_LIMIT) __trap(); }
      };
      mbar_wait(own, l);
      STAMP(2 + h, l * 16 + 5);
      if (lane == 0) {
        bulk_s2g(hb + r * 1536, sb + SM_RING + (2 * h) * SLOT + 16384, 8192); bulk_s2g(hb + r * 1536 + 512, sb + SM_RING + (2 * h + 1) * SLOT + 16384, 8192);
        bulk_commit(); bulk_wait_read<0>();
      }
      __syncwarp();
      set_flags(flags + r * 8, ev + 3, lane);
      STAMP(2 + h, l * 16 + 6);
      mbar_wait(afree + 8, l);
      wait_h(1, ev + 3); fetch_h(1, 0, 0); fetch_h(1, 1, 1);
      STAMP(2 + h, l * 16 + 13);
      wait_h(6, ev + 3); fetch_h(2, 0, 2); fetch_h(2, 1, 3);
      mbar_wait(afree, p0); p0 ^= 1;
      fetch_h(3, 0, 4); fetch_h(3, 1, 5);
      mbar_wait(own + 8, l);
      if (lane == 0) { bulk_s2g(hb + r * 1536 + 1024, abase + 7 * 8192, 6144); bulk_commit(); bulk_wait_read<0>(); }
      __syncwarp();
      set_flags(flags + r * 8, ev + 4, lane);
      wait_h(7, ev + 4); fetch_h(1, 2, 6);
      mbar_wait(afree + 16, l);
      fetch_h(2, 2, 0); fetch_h(3, 2, 1);
      __syncwarp();
      STAMP(2 + h, l * 16 + 7);
      if (l == 0) {
        mbar_wait(afree, p0); p0 ^= 1;
        STAMP(2 + h, l * 16 + 8);
        fetch_chunks(g_act + (2 * 32 + half) * 4096, flags, abase, afull, r, ev + 6, lane);
        STAMP(2 + h, l * 16 + 9);
        gather_stats(g_stats + (2 * 32 + half) * 512, sb + SM_STAT + h * 512, sb + B_STAT + h * 8, lane, tag);
      } else {
        mbar_wait(own + 16, 0);
        if (lane == 0) { tma_store(&tm_out, abase, 64 * r, 128 * cb + 64 * h); bulk_commit(); bulk_wait<0>(); }
      }
      STAMP(2 + h, l * 16 + 10);
    }
  } else {
    if (lane < 24) { g_kv[(0 * 8 + r) * 384 + cb * 24 + lane] = make_float4(0.f, 0.f, 0.f, 0.f); g_kv[(1 * 8 + r) * 384 + cb * 24 + lane] = make_float4(0.f, 0.f, 0.f, 0.f); }
    fence_gpu();
    const uint32_t tag = (epoch & 1) ^ 1;
    colsum_task(wqkv + 64 * r + 8 * (lane & 7), 3 * kD, true, 32 * cb, g_cs + ((r * 2 + 0) * 16 + cb) * 48 + 2 * (lane & 7), lane, tag);
    __nanosleep(500);
    colsum_gather(g_cs + (r * 2 + 0) * 16 * 48, sb + SM_CS, 48, lane, tag);
    fence_gpu();
    if (lane == 0) mbar_arrive(sb + B_CSRDY);
    STAMP(2, 48);
    if (lane == 1) prefetch_l2((const char*)wo + bid * 4096, 4096);
    if (lane == 2) prefetch_l2((const char*)w2 + bid * 11008, 11008);
    asm volatile("barrier.cluster.wait.aligned;" ::: "memory");
#pragma unroll 1
    for (int l = 0; l < 2; l++) {
      mbar_wait(sb + B_KVDONE, l);
      STAMP(2, 50 + l * 4);
      const float4* kv = g_kv + (l * 8 + r) * 384 + lane;
      float4 v[12];
      uint32_t cnt = 0;
      __nanosleep(KVDELAY);
      {
        const float4* pp = g_kv + (l * 8 + r) * 384 + (lane & 3) * 96 + 95;
        while (!__all_sync(0xffffffff, ld_relaxed_f4(pp).w == 16.f)) { if (++cnt > SPIN_LIMIT) __trap(); __nanosleep(KVSLEEP); }
      }
      STAMP(2, 51 + l * 4);
      while (true) {
        bool ok = true;
#pragma unroll
        for (int i = 0; i < 12; i++) v[i] = ld_relaxed_f4(kv + i * 32);
#pragma unroll
        for (int i = 0; i < 12; i++) ok = ok && v[i].w == 16.f;
        if (__all_sync(0xffffffff, ok)) break;
        if (++cnt > SPIN_LIMIT) __trap();
      }
      STAMP(2, 52 + l * 4);
#pragma unroll
      for (int hh = 0; hh < 4; hh++) {
        const float4 a = v[3 * hh], b = v[3 * hh + 1], c = v[3 * hh + 2];
        const float z0 = __shfl_sync(0xffffffff, c.z, lane & 3), z1 = __shfl_sync(0xffffffff, c.z, 4 + (lane & 3)),
                    z2 = __shfl_sync(0xffffffff, c.z, 8 + (lane & 3)), z3 = __shfl_sync(0xffffffff, c.z, 12 + (lane & 3));
        const uint32_t d = sb + SM_RING + 16384 + hh * 768 + lane * 8;
        sts_u2(d, pack_bf16(a.x, a.y), pack_bf16(a.z, b.x));
        sts_u2(d + 256, pack_bf16(b.y, b.z), pack_bf16(c.x, c.y));
        sts_u2(d + 512, pack_bf16(z0, z1), pack_bf16(z2, z3));
      }
      __syncwarp();
      if (lane == 0) mbar_arrive(sb + B_KVRDY);
      STAMP(2, 53 + l * 4);
      if (l == 0) {
        colsum_gather(g_cs + (r * 2 + 1) * 16 * 48, sb + SM_CS + 768, 44, lane, tag);
        if (lane == 0) mbar_arrive(sb + B_CSRDY + 8);
      }
    }
    if (lane == 0) g_epoch[bid * 8] = epoch + 1;
  }
  } else {
    asm volatile("setmaxnreg.inc.sync.aligned.u32 200;");
    const int lane = __shfl_sync(0xffffffff, threadIdx.x & 31, threadIdx.x & 31);
    const uint32_t epoch = ld_relaxed(g_epoch + bid * 8);
    const int wg0 = warp >> 2, lane0 = lane, half = cb * 2 + wg0, wg = wg0;
    const uint32_t sb0 = sb;
    STAMP(wg, 62);
    const uint32_t tag = (epoch + 1) & 1;
    uint32_t xr[16];
    uint32_t sph = 0;
    mbar_wait(sb0 + B_AFULL + wg0 * 64, 0);
#pragma unroll
    for (int s = 0; s < 4; s++)
      ldsm4(sb0 + wg0 * 65536 + (16 * (warp & 3) + 8 * ((lane0 >> 3) & 1) + (lane0 & 7)) * 128 + (((2 * s + (lane0 >> 4)) ^ (lane0 & 7)) << 4),
            xr[4 * s], xr[4 * s + 1], xr[4 * s + 2], xr[4 * s + 3]);
    asm volatile("barrier.cluster.wait.aligned;" ::: "memory");
    STAMP(wg, 63);

#pragma unroll 1
    for (int l = 0; l < 2; l++) {
      const uint32_t sb = opaque(sb0);
      const int lane = opaque(lane0), wg = opaque(wg0), wq = opaque(warp) & 3, g = lane >> 2, t = lane & 3;
      const uint32_t abase = sb + wg * 65536, afull = sb + B_AFULL + wg * 64, afree = sb + B_AFREE + wg * 24, own = sb + B_OWN + wg * 24;
      const uint32_t ring = sb + SM_RING, spare = ring + (2 * wg) * SLOT + 16384;
      const uint32_t dA = desc_lo(abase, 16), dH = desc_lo(abase, 1024), dB = desc_lo(ring, 8192), dS = desc_lo(spare, 1024);
      constexpr int S4 = SLOT >> 4;
      const uint32_t ev = epoch * 16 + l * 6;
      uint32_t swa[4];
#pragma unroll
      for (int s = 0; s < 4; s++) swa[s] = abase + (16 * wq + 8 * ((lane >> 3) & 1) + (lane & 7)) * 128 + (((2 * s + (lane >> 4)) ^ (lane & 7)) << 4);
      auto wait_b = [&](int st) { mbar_wait(sb + B_BFULL + (st & 3) * 8, (st >> 2) & 1); };
      auto release_b = [&](int st) { if (lane == 0) mbar_arrive(sb + B_BEMPTY + (st & 3) * 8); };
      auto signal = [&](uint32_t bar) { __syncwarp(); if (lane == 0) mbar_arrive(bar); };
      auto apar = [&](int s, int ph) -> uint32_t {
        const int uses = (s > NLL ? 3 : 0) + (s < 2 ? 2 : s < 7 ? 1 : 0);
        return ((l & uses) ^ (s > NLL ? ph : ph - 2)) & 1;
      };
      const uint32_t chk = abase + (16 * wq + g) * 128 + (((2 * t) ^ g) << 4);
      const uint32_t lin = abase + wq * 2048 + lane * 16;
      auto bad_chunk = [&](int i, uint32_t tg) -> uint32_t { return (lds_u32(chk + i * 8192) ^ tg) | (lds_u32(chk + (i * 8192 + 1024)) ^ tg); };
      auto refetch = [&](int i, int n, int buf, uint32_t tg) {
#pragma unroll 1
        for (int u = i; u < i + n; u++) {
          const uint4* src = g_act + (buf * 32 + opaque(half)) * 4096 + ((opaque(r) + u) & 7) * 512 + wq * 128 + opaque(lane);
          uint32_t cnt = 0;
          while (!__all_sync(0xffffffff, (bad_chunk(u, tg) & 1u) == 0)) {
#pragma unroll 1
            for (int v = 0; v < 4; v++) sts_u4(lin + u * 8192 + v * 512, ld_relaxed_u4(src + v * 32));
            fence_async_smem();
            __syncwarp();
            HEALCNT();
            if (++cnt > SPIN_LIMIT) __trap();
          }
        }
      };
      auto fetch_ok = [&](int i, int n, int ph, int buf, uint32_t tg) {
        uint32_t bad = 0;
#pragma unroll
        for (int u = i; u < i + n; u++) mbar_wait(afull + u * 8, apar(u, ph));
#pragma unroll
        for (int u = i; u < i + n; u++) bad |= bad_chunk(u, tg);
        if (__builtin_expect(!__all_sync(0xffffffff, (bad & 1u) == 0), 0)) refetch(i, n, buf, tg);
      };
      auto fetch_direct = [&](int buf, uint32_t e, uint32_t tg) {
        const uint32_t* f = (const uint32_t*)(g_flags + ((opaque(half) * 8 + opaque(r)) * 8 + ((r + 1 + lane % NLL) & 7)) * 8 + wq * 2);
        uint32_t cnt = 0;
        while (!__all_sync(0xffffffff, (int32_t)(ld_relaxed(f) - e) >= 0)) { if (++cnt > SPIN_LIMIT) __trap(); }
        const uint4* src = g_act + (buf * 32 + opaque(half)) * 4096 + wq * 128 + lane;
        uint4 v[NLL * 4];
#pragma unroll
        for (int u = 0; u < NLL * 4; u++) v[u] = ld_relaxed_u4(src + ((r + 1 + u / 4) & 7) * 512 + (u & 3) * 32);
#pragma unroll
        for (int u = 0; u < NLL * 4; u++) sts_u4(lin + (1 + u / 4) * 8192 + (u & 3) * 512, v[u]);
        fence_async_smem();
        __syncwarp();
        uint32_t bad = 0;
#pragma unroll
        for (int u = 1; u <= NLL; u++) bad |= bad_chunk(u, tg);
        if (__builtin_expect(!__all_sync(0xffffffff, (bad & 1u) == 0), 0)) refetch(1, NLL, buf, tg);
      };
      const uint32_t hchk = abase + (lane >> 4) * 2048 + ((lane >> 3) & 1) * 1024 + (2 * wq + ((lane >> 2) & 1)) * 128 + (lane & 3) * 32 + g * 4;
      const uint32_t hchk3 = hchk + (lane >= 16 ? 0 : 4096);
      auto bad_block = [&](int slot, bool three, uint32_t tg) -> uint32_t {
        return (lds_u32(hchk + slot * 8192) ^ tg) | (lds_u32(three ? hchk3 + slot * 8192 : hchk + (slot * 8192 + 4096)) ^ tg);
      };
      auto refetch_h = [&](int slot, int ts, int bb, uint32_t tg) {
        const int ln = opaque(lane);
        const uint32_t off = (ln >> 4) * 1024 + wq * 256 + (ln & 15) * 16;
        const uint4* src = g_h + (opaque(half) * 8 + ((opaque(r) + 2 * ts) & 7)) * 1536 + bb * 512 + off / 16;
        uint32_t cnt = 0;
        while (!__all_sync(0xffffffff, (bad_block(slot, bb == 2, tg) >> 31) == 0)) {
#pragma unroll 1
          for (int v = 0; v < (bb == 2 ? 3 : 4); v++) sts_u4(abase + slot * 8192 + v * 2048 + off, ld_relaxed_u4(src + v * 128));
          fence_async_smem();
          __syncwarp();
          HEALCNT();
          if (++cnt > SPIN_LIMIT) __trap();
        }
      };
      const uint32_t tmask = t == 0 ? 1u : 0u;
      auto store_chunk = [&](const uint32_t (&v)[16], uint32_t tg  , uint32_t msk) {
#pragma unroll
        for (int s = 0; s < 4; s++) stsm4(swa[s], (v[4 * s] & ~msk) | tg, (v[4 * s + 1] & ~msk) | tg, v[4 * s + 2], v[4 * s + 3]);
      };
      auto publish_chunk = [&](int buf, uint32_t e) {
        __syncwarp();
        uint4 v[4];
#pragma unroll
        for (int u = 0; u < 4; u++) v[u] = lds_u4(lin + u * 512);
        uint4* dst = g_act + (buf * 32 + opaque(half)) * 4096 + opaque(r) * 512 + wq * 128 + lane;
#pragma unroll
        for (int u = 0; u < 4; u++) st_relaxed_u4(dst + u * 32, v[u]);
        set_flags(g_flags + opaque(half) * 512 + opaque(r) * 8 + wq * 2, e, lane);
        fence_async_smem();
        wg_bar(wg);
      };
      auto stat_dst = [&](int ln) -> float2* { return g_stats + (ln * 32 + opaque(half)) * 512 + opaque(r) * 64 + 16 * wq + g; };
      const uint32_t stat_sm = sb + SM_STAT + (wg * 64 + 16 * wq + g) * 8;
      const uint32_t cs_sm = sb + SM_CS + 8 * t;
      const uint32_t ltag = l ^ 1;
      float rs0, rs1;
      {
        float ak[32], av[32], aq[32];
        STAMP(wg, l * 24 + 0);
        wait_b(0);
        wg_fence();
        wgmma_n128_init<0, 0, HI_SW>(ak, av, dA, dB);
        static_for<1, 4>([&](auto K) { wgmma_n128<2 * K.value, 128 * K.value, HI_SW>(ak, av, dA, dB); });
        wg_commit();
        publish_stats(xr, stat_dst(2 * l), t, tag);
        if (l == 1) fetch_direct(2, ev, tag);
        static_for<1, 8>([&](auto I) {
          constexpr int i = I.value;
          if (l == 0) mbar_wait(afull + i * 8, 0); else if (i > NLL) fetch_ok(i, 1, 0, 2, tag);
          if (i == 1) STAMP(wg, l * 2 + 19);
          wait_b(i);
          wg_fence();
          static_for<0, 4>([&](auto K) { wgmma_n128<i * 512 + 2 * K.value, (i & 3) * S4 + 128 * K.value, HI_SW>(ak, av, dA, dB); });
          wg_commit();
          wg_wait<1>(); release_b(i - 1);
        });
        STAMP(wg, l * 24 + 1);
        if (l == 0) mbar_wait(sb + B_CSRDY, 0);
        mbar_wait(sb + B_STAT + wg * 8, sph); sph ^= 1;
        const float2 s0 = lds_f2(stat_sm), s1 = lds_f2(stat_sm + 64);
        const float y0 = s0.x * 1.4426950408889634f, y1 = s1.x * 1.4426950408889634f;
        {
          float2 c[16];
#pragma unroll
          for (int j = 0; j < 16; j++) c[j] = lds_f2(cs_sm + (64 + 8 * j) * 4);
          wg_wait<0>(); release_b(7);
          fence_regs(ak); fence_regs(av);
          STAMP(wg, l * 24 + 2);
          uint32_t pk[16], pv[16];
#pragma unroll
          for (int j = 0; j < 8; j++) {
            pk[2 * j] = pack_bf16(phi_y(y0 * fmaf(s0.y, c[j].x, ak[4 * j])), phi_y(y0 * fmaf(s0.y, c[j].y, ak[4 * j + 1])));
            pk[2 * j + 1] = pack_bf16(phi_y(y1 * fmaf(s1.y, c[j].x, ak[4 * j + 2])), phi_y(y1 * fmaf(s1.y, c[j].y, ak[4 * j + 3])));
            pv[2 * j] = pack_bf16(s0.x * fmaf(s0.y, c[8 + j].x, av[4 * j]), s0.x * fmaf(s0.y, c[8 + j].y, av[4 * j + 1]));
            pv[2 * j + 1] = pack_bf16(s1.x * fmaf(s1.y, c[8 + j].x, av[4 * j + 2]), s1.x * fmaf(s1.y, c[8 + j].y, av[4 * j + 3]));
          }
#pragma unroll
          for (int s = 0; s < 4; s++) {
            stsm4(swa[s] + (spare - abase), pk[4 * s], pk[4 * s + 1], pk[4 * s + 2], pk[4 * s + 3]);
            stsm4(swa[s] + (spare - abase) + SLOT, pv[4 * s], pv[4 * s + 1], pv[4 * s + 2], pv[4 * s + 3]);
          }
        }
        STAMP(wg, 20 + l * 2);
        if (wg == 0) { asm volatile("bar.arrive 4, 256;" ::: "memory"); asm volatile("bar.sync 5, 256;" ::: "memory"); }
        else {
          asm volatile("bar.sync 4, 256;" ::: "memory");
          float c0[4] = {0.f, 0.f, 0.f, 0.f}, c1[4] = {0.f, 0.f, 0.f, 0.f}, z0[4] = {0.f, 0.f, 0.f, 0.f}, z1[4] = {0.f, 0.f, 0.f, 0.f};
          const int m = lane >> 3;
          const uint32_t va = ring + SLOT + 16384 + (8 * (m >> 1) + (lane & 7)) * 128 + (((2 * wq + (m & 1)) ^ (lane & 7)) << 4);
          const uint32_t pa = ring + 16384 + (8 * (m & 1) + (lane & 7)) * 128 + (((2 * wq + (m >> 1)) ^ (lane & 7)) << 4);
#pragma unroll
          for (int ks = 0; ks < 8; ks++) {
            uint32_t a0, a1, a2, a3, b0, b1, b2, b3;
            ldsm4t(va + (ks >> 2) * 2 * SLOT + (ks & 3) * 2048, a0, a1, a2, a3);
            ldsm4t(pa + (ks >> 2) * 2 * SLOT + (ks & 3) * 2048, b0, b1, b2, b3);
            mma16816(c0, a0, a1, a2, a3, b0, b1);
            mma16816(c1, a0, a1, a2, a3, b2, b3);
            mma16816(z0, 0x3f803f80u, 0x3f803f80u, 0x3f803f80u, 0x3f803f80u, b0, b1);
            mma16816(z1, 0x3f803f80u, 0x3f803f80u, 0x3f803f80u, 0x3f803f80u, b2, b3);
          }
          asm volatile("bar.arrive 5, 256;" ::: "memory");
          float* kv = (float*)(g_kv + (l * 8 + opaque(r)) * 384 + wq * 96 + lane);
          red_add_f4(kv, c0[0], c0[1], c1[0], 1.f);
          red_add_f4(kv + 128, c1[1], c0[2], c0[3], 1.f);
          red_add_f4(kv + 256, c1[2], c1[3], g == 0 ? z0[0] : g == 1 ? z0[1] : g == 2 ? z1[0] : z1[1], 1.f);
          signal(sb + B_KVDONE);
        }
        STAMP(wg, l * 24 + 3);
        static_for<0, 4>([&](auto I) {
          constexpr int i = I.value;
          wait_b(8 + i);
          wg_fence();
          static_for<0, 8>([&](auto K) {
            constexpr int k = K.value;
            if constexpr (i == 0 && k == 0) wgmma_n64_init<0, 0, HI_SW>(aq, dA, dB);
            else wgmma_n64<i * 1024 + (k >> 2) * 512 + 2 * (k & 3), i * S4 + 128 * k, HI_SW>(aq, dA, dB);
          });
          wg_commit();
        });
        float2 c[8];
#pragma unroll
        for (int j = 0; j < 8; j++) c[j] = lds_f2(cs_sm + 8 * j * 4);
        wg_wait<3>(); release_b(8);
        wg_wait<2>(); release_b(9);
        wg_wait<1>(); release_b(10);
        wg_wait<0>(); release_b(11);
        fence_regs(aq);
        if (lane == 0) mbar_arrive(afree);
        STAMP(wg, l * 24 + 4);
        uint32_t pq[16];
#pragma unroll
        for (int j = 0; j < 8; j++) {
          pq[2 * j] = pack_bf16(phi_y(y0 * fmaf(s0.y, c[j].x, aq[4 * j])), phi_y(y0 * fmaf(s0.y, c[j].y, aq[4 * j + 1])));
          pq[2 * j + 1] = pack_bf16(phi_y(y1 * fmaf(s1.y, c[j].x, aq[4 * j + 2])), phi_y(y1 * fmaf(s1.y, c[j].y, aq[4 * j + 3])));
        }
        STAMP(wg, l * 24 + 5);
        mbar_wait(sb + B_KVRDY, l);
        STAMP(wg, l * 24 + 6);
        uint2 f[12];
#pragma unroll
        for (int i = 0; i < 12; i++) f[i] = lds_u2(ring + 16384 + i * 256 + lane * 8);
        float cn[4][8], cz[4][4];
#pragma unroll
        for (int hh = 0; hh < 4; hh++) {
          float c0[4] = {0.f, 0.f, 0.f, 0.f}, c1[4] = {0.f, 0.f, 0.f, 0.f};
          cz[hh][0] = cz[hh][1] = cz[hh][2] = cz[hh][3] = 0.f;
          mma16816(cz[hh], pq[4 * hh], pq[4 * hh + 1], pq[4 * hh + 2], pq[4 * hh + 3], f[3 * hh + 2].x, f[3 * hh + 2].y);
          mma16816(c0, pq[4 * hh], pq[4 * hh + 1], pq[4 * hh + 2], pq[4 * hh + 3], f[3 * hh].x, f[3 * hh].y);
          mma16816(c1, pq[4 * hh], pq[4 * hh + 1], pq[4 * hh + 2], pq[4 * hh + 3], f[3 * hh + 1].x, f[3 * hh + 1].y);
#pragma unroll
          for (int u = 0; u < 4; u++) { cn[hh][u] = c0[u]; cn[hh][4 + u] = c1[u]; }
        }
        uint32_t o[16];
#pragma unroll
        for (int hh = 0; hh < 4; hh++) {
          const float i0 = rcp(cz[hh][0] + 1e-6f), i1 = rcp(cz[hh][2] + 1e-6f);
          o[4 * hh] = pack_bf16(cn[hh][0] * i0, cn[hh][1] * i0); o[4 * hh + 1] = pack_bf16(cn[hh][2] * i1, cn[hh][3] * i1);
          o[4 * hh + 2] = pack_bf16(cn[hh][4] * i0, cn[hh][5] * i0); o[4 * hh + 3] = pack_bf16(cn[hh][6] * i1, cn[hh][7] * i1);
        }
        store_chunk(o, ltag & tmask, tmask);
        publish_chunk(0, ev + 1);
        STAMP(wg, l * 24 + 7);
      }
      {
        float acc[32];
        wait_b(12);
        wg_fence();
        wgmma_n64_init<0, 0, HI_SW>(acc, dA, dB);
        static_for<1, 4>([&](auto K) { wgmma_n64<2 * K.value, 128 * K.value, HI_SW>(acc, dA, dB); });
        wg_commit();
        fetch_direct(0, ev + 1, ltag);
        static_for<1, 8>([&](auto I) {
          constexpr int i = I.value;
          if ((i & 1) == 0) wait_b(12 + i / 2);
          if (i > NLL && (i == NLL + 1 || (i & 1) == 0)) fetch_ok(i, (i & 1) ? 1 : 2, 1, 0, ltag);
          if (i == 1) STAMP(wg, l * 24 + 8);
          if (l == 1) STAMP(wg, 43 + i);
          wg_fence();
          static_for<0, 4>([&](auto K) { wgmma_n64<i * 512 + 2 * K.value, (i / 2) * S4 + (i & 1) * 512 + 128 * K.value, HI_SW>(acc, dA, dB); });
          wg_commit();
          if ((i & 1) == 0) { wg_wait<1>(); release_b(11 + i / 2); }
        });
        wg_wait<0>(); release_b(15);
        fence_regs(acc);
        if (lane == 0) mbar_arrive(afree);
        STAMP(wg, l * 24 + 9);
#pragma unroll
        for (int j = 0; j < 8; j++) {
          xr[2 * j] = pack_bf16(bf_lo(xr[2 * j]) + acc[4 * j], bf_hi(xr[2 * j]) + acc[4 * j + 1]);
          xr[2 * j + 1] = pack_bf16(bf_lo(xr[2 * j + 1]) + acc[4 * j + 2], bf_hi(xr[2 * j + 1]) + acc[4 * j + 3]);
        }
        store_chunk(xr, ltag & tmask, tmask);
        publish_chunk(1, ev + 2);
        STAMP(wg, l * 24 + 10);
      }
      float ap[32], ao[32];
      {
        float h0[32], h1[32], h2[24];
        wait_b(16);
        wg_fence();
        wgmma_n128_init<0, 0, HI_SW>(h0, h1, dA, dB);
        static_for<1, 4>([&](auto K) { wgmma_n128<2 * K.value, 128 * K.value, HI_SW>(h0, h1, dA, dB); });
        wg_commit();
        publish_stats(xr, stat_dst(2 * l + 1), t, tag);
        fetch_direct(1, ev + 2, ltag);
        static_for<1, 8>([&](auto I) {
          constexpr int i = I.value;
          if (i > NLL) fetch_ok(i, 1, 2, 1, ltag);
          if (i == 1) STAMP(wg, l * 24 + 11);
          wait_b(16 + i);
          wg_fence();
          static_for<0, 4>([&](auto K) { wgmma_n128<i * 512 + 2 * K.value, (i & 3) * S4 + 128 * K.value, HI_SW>(h0, h1, dA, dB); });
          wg_commit();
          wg_wait<1>(); release_b(15 + i);
        });
        auto up2 = [&](auto I) {
          constexpr int i = I.value;
          wait_b(24 + i);
          wg_fence();
          static_for<0, 8>([&](auto K) {
            constexpr int k = K.value;
            if constexpr (i == 0 && k == 0) wgmma_n48_init<0, 0, HI_SW>(h2, dA, dB);
            else wgmma_n48<i * 1024 + (k >> 2) * 512 + 2 * (k & 3), i * S4 + 128 * k, HI_SW>(h2, dA, dB);
          });
          wg_commit();
        };
        up2(IC<0>{});
        if (l == 0) mbar_wait(sb + B_CSRDY + 8, 0);
        mbar_wait(sb + B_STAT + wg * 8, sph); sph ^= 1;
        const float2 s0 = lds_f2(stat_sm), s1 = lds_f2(stat_sm + 64);
        float2 c[22];
#pragma unroll
        for (int j = 0; j < 22; j++) c[j] = lds_f2(cs_sm + (192 + 8 * j) * 4);
        const uint32_t sgn = ltag ? 0x80008000u : 0u;
        rs0 = ltag ? -s0.x : s0.x; rs1 = ltag ? -s1.x : s1.x;
        wg_wait<1>(); release_b(23);
        up2(IC<1>{});
        fence_regs(h0); fence_regs(h1);
        STAMP(wg, l * 24 + 12);
        const uint32_t hoff = (lane >> 4) * 1024 + (2 * wq + ((lane >> 3) & 1)) * 128 + (lane & 7) * 16;
        auto store_h = [&](const float* a, const float2* cc, int nt, uint32_t dst) {
          uint32_t p[16];
#pragma unroll
          for (int j = 0; j < nt; j++) {
            p[2 * j] = pack_bf16_relu(fmaf(s0.y, cc[j].x, a[4 * j]), fmaf(s0.y, cc[j].y, a[4 * j + 1])) ^ sgn;
            p[2 * j + 1] = pack_bf16_relu(fmaf(s1.y, cc[j].x, a[4 * j + 2]), fmaf(s1.y, cc[j].y, a[4 * j + 3])) ^ sgn;
          }
#pragma unroll
          for (int s = 0; s < nt / 2; s++) stsm4(dst + s * 2048, p[4 * s], p[4 * s + 1], p[4 * s + 2], p[4 * s + 3]);
        };
        store_h(h0, c, 8, spare + hoff);
        up2(IC<2>{});
        store_h(h1, c + 8, 8, spare + SLOT + hoff);
        fence_async_smem(); signal(own);
        STAMP(wg, l * 24 + 13);
        up2(IC<3>{});
        wg_wait<3>(); release_b(24);
        wg_wait<2>(); release_b(25);
        if (lane == 0) mbar_arrive(afree + 8);
        wg_bar(wg);
        wait_b(28);
        wg_fence();
        wgmma_n128_init<0, 0, HI_NS>(ap, ao, dS, dB);
        static_for<1, 4>([&](auto K) { wgmma_n128<128 * K.value, 128 * K.value, HI_NS>(ap, ao, dS, dB); });
        wg_commit();
        wg_wait<2>(); release_b(26);
        wg_wait<1>(); release_b(27);
        fence_regs(h2);
        if (lane == 0) mbar_arrive(afree);
        wait_b(29);
        wg_fence();
        static_for<0, 4>([&](auto K) { wgmma_n128<S4 + 128 * K.value, S4 + 128 * K.value, HI_NS>(ap, ao, dS, dB); });
        wg_commit();
        wg_bar(wg);
        store_h(h2, c + 16, 6, abase + 7 * 8192 + hoff);
        fence_async_smem(); signal(own + 8);
        wg_wait<1>(); release_b(28);
        wg_bar(wg);
        STAMP(wg, l * 24 + 23);
      }
      {
        float bp[32], bo[32];
        const uint32_t htag = ltag << 31;
        wait_b(30);
        wg_fence();
        static_for<0, 3>([&](auto K) { wgmma_n128<7 * 512 + 128 * K.value, 2 * S4 + 128 * K.value, HI_NS>(ap, ao, dH, dB); });
        wg_commit();
        wg_wait<1>(); release_b(29);
        static_for<0, 6>([&](auto I) {
          constexpr int i = I.value;
          mbar_wait(afull + i * 8, apar(i, 3));
          if (__builtin_expect(!__all_sync(0xffffffff, (bad_block(i, false, htag) >> 31) == 0), 0)) refetch_h(i, 1 + i / 2, i & 1, htag);
          if (i == 0) STAMP(wg, l * 24 + 14);
          if (l == 1) STAMP(wg, 51 + i);
          wait_b(31 + i);
          wg_fence();
          static_for<0, 4>([&](auto K) { wgmma_n128<i * 512 + 128 * K.value, ((31 + i) & 3) * S4 + 128 * K.value, HI_NS>(ap, ao, dH, dB); });
          wg_commit();
          wg_wait<1>(); release_b(30 + i);
          if (i == 2 && lane == 0) mbar_arrive(afree + 16);
          if (i == 3 && lane == 0) { mbar_arrive_remote(mapa(sb + B_PFREE + wg * 8, (r & 1) ^ 1)); if (wq == 0) mbar_expect_tx(sb + B_PRDY + wg * 8, 8192); }
        });
        mbar_wait(afull + 6 * 8, apar(6, 3)); mbar_wait(afull, apar(0, 4)); mbar_wait(afull + 8, apar(1, 4));
        if (__builtin_expect(!__all_sync(0xffffffff, ((bad_block(6, true, htag) | bad_block(0, true, htag) | bad_block(1, true, htag)) >> 31) == 0), 0)) {
          refetch_h(6, 1, 2, htag); refetch_h(0, 2, 2, htag); refetch_h(1, 3, 2, htag);
        }
        if (l == 1) STAMP(wg, 57);
        wait_b(37); wait_b(38); wait_b(39);
        if (l == 1) STAMP(wg, 58);
        wg_fence();
        static_for<0, 9>([&](auto K) {
          constexpr int b = K.value / 3, k = K.value % 3, oa = (b == 0 ? 6 : b - 1) * 512 + 128 * k, ob = (1 + b) * S4 + 128 * k;
          if constexpr (K.value == 0) wgmma_n64_init<oa, ob, HI_NS>(bp, dH, dB); else wgmma_n64<oa, ob, HI_NS>(bp, dH, dB);
        });
        wg_commit();
        static_for<0, 9>([&](auto K) {
          constexpr int b = K.value / 3, k = K.value % 3, oa = (b == 0 ? 6 : b - 1) * 512 + 128 * k, ob = (1 + b) * S4 + 512 + 128 * k;
          if constexpr (K.value == 0) wgmma_n64_init<oa, ob, HI_NS>(bo, dH, dB); else wgmma_n64<oa, ob, HI_NS>(bo, dH, dB);
        });
        wg_commit();
        wg_wait<2>(); release_b(36);
        wg_wait<1>();
        fence_regs(ap); fence_regs(ao); fence_regs(bp);
        STAMP(wg, l * 24 + 15);
        mbar_wait(sb + B_PFREE + wg * 8, l);
        const uint32_t rdst = mapa(abase + 2 * 8192 + (wq * 32 + lane) * 16, (r & 1) ^ 1), rbar = mapa(sb + B_PRDY + wg * 8, (r & 1) ^ 1);
#pragma unroll
        for (int i = 0; i < 4; i++)
          st_async_v4(rdst + i * 2048, pack_bf16(ap[8 * i] + bp[8 * i], ap[8 * i + 1] + bp[8 * i + 1]), pack_bf16(ap[8 * i + 2] + bp[8 * i + 2], ap[8 * i + 3] + bp[8 * i + 3]),
                      pack_bf16(ap[8 * i + 4] + bp[8 * i + 4], ap[8 * i + 5] + bp[8 * i + 5]), pack_bf16(ap[8 * i + 6] + bp[8 * i + 6], ap[8 * i + 7] + bp[8 * i + 7]), rbar);
        wg_wait<0>(); release_b(37); release_b(38); release_b(39);
        fence_regs(bo);
#pragma unroll
        for (int i = 0; i < 32; i++) ao[i] += bo[i];
        wg_bar(wg);
        STAMP(wg, l * 24 + 16);
        mbar_wait(sb + B_PRDY + wg * 8, l);
        STAMP(wg, l * 24 + 17);
        uint4 p[4];
#pragma unroll
        for (int i = 0; i < 4; i++) p[i] = lds_u4(abase + 2 * 8192 + i * 2048 + (wq * 32 + lane) * 16);
#pragma unroll
        for (int i = 0; i < 4; i++) {
          xr[4 * i] = pack_bf16(fmaf(rs0, ao[8 * i] + bf_lo(p[i].x), bf_lo(xr[4 * i])), fmaf(rs0, ao[8 * i + 1] + bf_hi(p[i].x), bf_hi(xr[4 * i])));
          xr[4 * i + 1] = pack_bf16(fmaf(rs1, ao[8 * i + 2] + bf_lo(p[i].y), bf_lo(xr[4 * i + 1])), fmaf(rs1, ao[8 * i + 3] + bf_hi(p[i].y), bf_hi(xr[4 * i + 1])));
          xr[4 * i + 2] = pack_bf16(fmaf(rs0, ao[8 * i + 4] + bf_lo(p[i].z), bf_lo(xr[4 * i + 2])), fmaf(rs0, ao[8 * i + 5] + bf_hi(p[i].z), bf_hi(xr[4 * i + 2])));
          xr[4 * i + 3] = pack_bf16(fmaf(rs1, ao[8 * i + 6] + bf_lo(p[i].w), bf_lo(xr[4 * i + 3])), fmaf(rs1, ao[8 * i + 7] + bf_hi(p[i].w), bf_hi(xr[4 * i + 3])));
        }
        if (l == 0) {
          signal(afree);
          store_chunk(xr, tag & tmask, tmask);
          publish_chunk(2, ev + 6);
        } else {
          store_chunk(xr, 0u, 0u);
          fence_async_smem(); signal(own + 16);
        }
        STAMP(wg, l * 24 + 18);
      }
    }

  }
}

typedef CUresult (*EncodeFn)(CUtensorMap*, CUtensorMapDataType, cuuint32_t, void*, const cuuint64_t*, const cuuint64_t*, const cuuint32_t*,
                             const cuuint32_t*, CUtensorMapInterleave, CUtensorMapSwizzle, CUtensorMapL2promotion, CUtensorMapFloatOOBfill);

CUtensorMap make_map(EncodeFn enc, const void* ptr, uint64_t cols, uint64_t rows, uint32_t box_rows) {
  CUtensorMap m;
  cuuint64_t gd[2] = {cols, rows}, gs[1] = {cols * 2};
  cuuint32_t bd[2] = {64, box_rows}, es[2] = {1, 1};
  enc(&m, CU_TENSOR_MAP_DATA_TYPE_BFLOAT16, 2, const_cast<void*>(ptr), gd, gs, bd, es, CU_TENSOR_MAP_INTERLEAVE_NONE,
      CU_TENSOR_MAP_SWIZZLE_128B, CU_TENSOR_MAP_L2_PROMOTION_L2_128B, CU_TENSOR_MAP_FLOAT_OOB_FILL_NONE);
  return m;
}

}

extern "C" void kernel_launch(void* const* d_in, const int* in_sizes, int n_in, void* d_out, int out_size) {
  (void)in_sizes; (void)n_in; (void)out_size;
  const __nv_bfloat16* x = (const __nv_bfloat16*)d_in[0];
  const __nv_bfloat16* wqkv = (const __nv_bfloat16*)d_in[1];
  const __nv_bfloat16* wo = (const __nv_bfloat16*)d_in[2];
  const __nv_bfloat16* w1 = (const __nv_bfloat16*)d_in[4];
  const __nv_bfloat16* w2 = (const __nv_bfloat16*)d_in[5];
  void* fn = nullptr;
  cudaDriverEntryPointQueryResult q;
  cudaGetDriverEntryPoint("cuTensorMapEncodeTiled", &fn, cudaEnableDefault, &q);
  EncodeFn enc = (EncodeFn)fn;
  const CUtensorMap tm_x = make_map(enc, x, kD, kS, 64), tm_out = make_map(enc, d_out, kD, kS, 64),
                    tm_wqkv = make_map(enc, wqkv, 3 * kD, kD, 64), tm_wo = make_map(enc, wo, kD, kD, 64),
                    tm_w1 = make_map(enc, w1, kFF, kD, 64), tm_w2 = make_map(enc, w2, kD, kFF, 64), tm_w2s = make_map(enc, w2, kD, kFF, 48);
  cudaFuncSetAttribute(fused_kernel, cudaFuncAttributeMaxDynamicSharedMemorySize, SM_TOTAL);
  fused_kernel<<<128, 384, SM_TOTAL>>>(tm_x, tm_out, tm_wqkv, tm_wo, tm_w1, tm_w2, tm_w2s, wqkv, wo, w1, w2);
}
```

```cpp
#include <cuda_runtime.h>
#include <cuda_bf16.h>
#include <cuda.h>
#include <stdint.h>

#define NOCHECK 0
#define NOFENCE 0
#define KVSLEEP 40
#define KVDELAY 600
#define PUBWAIT bulk_wait_read
#define PRIO 0
#define MAPPING 0
namespace {

constexpr int kS = 2048, kD = 512, kFF = 1376, kHS = 176;
constexpr uint32_t SM_RING = 131072, SLOT = 24576, SM_MISC = 229376;
constexpr uint32_t SM_STAT = SM_MISC;
constexpr uint32_t SM_CS = SM_MISC + 1024;
constexpr uint32_t SM_BAR = SM_CS + 1472;
constexpr uint32_t B_BFULL = SM_BAR, B_BEMPTY = SM_BAR + 32, B_AFULL = SM_BAR + 64  ,
                   B_AFREE = SM_BAR + 192  , B_OWN = SM_BAR + 240  , B_STAT = SM_BAR + 288  ,
                   B_CSRDY = SM_BAR + 304  , B_KVDONE = SM_BAR + 320, B_KVRDY = SM_BAR + 328,
                   B_PRDY = SM_BAR + 336  , B_PFREE = SM_BAR + 352  ;
constexpr uint32_t SM_TOTAL = SM_BAR + 368;
static_assert(SM_TOTAL <= 232448, "smem");
constexpr uint32_t SPIN_LIMIT = 1u << 22;

__device__ uint32_t g_epoch[128 * 8];
__device__ __align__(128) uint4 g_flags[32 * 8 * 8 * 2];
__device__ __align__(16) float4 g_cs[8 * 2 * 16 * 48];
__device__ __align__(128) float4 g_kv[2 * 8 * 384];
__device__ __align__(128) float2 g_stats[4 * 32 * 64 * 8];
__device__ __align__(1024) uint4 g_act[3 * 32 * 8 * 512];
__device__ __align__(1024) uint4 g_h[32 * 8 * 3 * 512];
#define HEALCNT() do {} while (0)
#define STAMP(role, i) do {} while (0)

__device__ __forceinline__ uint32_t smem_u32(const void* p) { return (uint32_t)__cvta_generic_to_shared(p); }
__device__ __forceinline__ void mbar_init(uint32_t bar, uint32_t cnt) { asm volatile("mbarrier.init.shared::cta.b64 [%0], %1;" :: "r"(bar), "r"(cnt)); }
__device__ __forceinline__ void mbar_expect_tx(uint32_t bar, uint32_t bytes) { asm volatile("mbarrier.arrive.expect_tx.shared::cta.b64 _, [%0], %1;" :: "r"(bar), "r"(bytes) : "memory"); }
__device__ __forceinline__ void mbar_arrive(uint32_t bar) { asm volatile("mbarrier.arrive.shared::cta.b64 _, [%0];" :: "r"(bar) : "memory"); }
__device__ __forceinline__ void mbar_arrive_remote(uint32_t bar) { asm volatile("mbarrier.arrive.shared::cluster.b64 _, [%0];" :: "r"(bar) : "memory"); }
__device__ __forceinline__ void mbar_wait(uint32_t bar, uint32_t parity) {
  asm volatile("{\n.reg .pred p;\n.reg .u32 c;\nmov.u32 c, 0;\nWAIT_LOOP:\n"
               "mbarrier.try_wait.parity.shared::cta.b64 p, [%0], %1;\n@p bra WAIT_DONE;\n"
               "add.u32 c, c, 1;\nsetp.lt.u32 p, c, %2;\n@p bra WAIT_LOOP;\ntrap;\nWAIT_DONE:\n}"
               :: "r"(bar), "r"(parity), "n"(SPIN_LIMIT) : "memory");
}
__device__ __forceinline__ uint32_t mapa(uint32_t addr, uint32_t rank) { uint32_t r; asm volatile("mapa.shared::cluster.u32 %0, %1, %2;" : "=r"(r) : "r"(addr), "r"(rank)); return r; }
__device__ __forceinline__ bool elect_one() { uint32_t p; asm volatile("{\n.reg .pred P;\nelect.sync _|P, 0xffffffff;\nselp.u32 %0, 1, 0, P;\n}" : "=r"(p)); return p; }
__device__ __forceinline__ void bulk_g2s(uint32_t dst, const void* src, uint32_t bytes, uint32_t bar) {
  asm volatile("cp.async.bulk.shared::cluster.global.mbarrier::complete_tx::bytes [%0], [%1], %2, [%3];" :: "r"(dst), "l"(src), "r"(bytes), "r"(bar) : "memory");
}
__device__ __forceinline__ void bulk_s2g(void* dst, uint32_t src, uint32_t bytes) { asm volatile("cp.async.bulk.global.shared::cta.bulk_group [%0], [%1], %2;" :: "l"(dst), "r"(src), "r"(bytes) : "memory"); }
__device__ __forceinline__ void bulk_commit() { asm volatile("cp.async.bulk.commit_group;" ::: "memory"); }
template <int N> __device__ __forceinline__ void bulk_wait_read() { asm volatile("cp.async.bulk.wait_group.read %0;" :: "n"(N) : "memory"); }
template <int N> __device__ __forceinline__ void bulk_wait() { asm volatile("cp.async.bulk.wait_group %0;" :: "n"(N) : "memory"); }
__device__ __forceinline__ void tma_load(uint32_t dst, const CUtensorMap* m, int c0, int c1, uint32_t bar) {
  asm volatile("cp.async.bulk.tensor.2d.shared::cluster.global.mbarrier::complete_tx::bytes [%0], [%1, {%3, %4}], [%2];" :: "r"(dst), "l"(m), "r"(bar), "r"(c0), "r"(c1) : "memory");
}
__device__ __forceinline__ void tma_store(const CUtensorMap* m, uint32_t src, int c0, int c1) {
  asm volatile("cp.async.bulk.tensor.2d.global.shared::cta.bulk_group [%0, {%2, %3}], [%1];" :: "l"(m), "r"(src), "r"(c0), "r"(c1) : "memory");
}
__device__ __forceinline__ void prefetch_l2(const void* p, uint32_t bytes) { asm volatile("cp.async.bulk.prefetch.L2.global [%0], %1;" :: "l"(p), "r"(bytes) : "memory"); }
__device__ __forceinline__ void prefetch_map(const CUtensorMap* m) { asm volatile("prefetch.tensormap [%0];" :: "l"(m) : "memory"); }
__device__ __forceinline__ void fence_async_smem() { asm volatile("fence.proxy.async.shared::cta;" ::: "memory"); }
__device__ __forceinline__ void fence_async_global() { asm volatile("fence.proxy.async.global;" ::: "memory"); }
__device__ __forceinline__ void fence_gpu() { asm volatile("fence.acq_rel.gpu;" ::: "memory"); }
__device__ __forceinline__ void st_release(uint32_t* p, uint32_t v) { asm volatile("st.release.gpu.global.u32 [%0], %1;" :: "l"(p), "r"(v) : "memory"); }
__device__ __forceinline__ uint32_t ld_acquire(const uint32_t* p) { uint32_t v; asm volatile("ld.acquire.gpu.global.u32 %0, [%1];" : "=r"(v) : "l"(p) : "memory"); return v; }
__device__ __forceinline__ uint32_t ld_relaxed(const uint32_t* p) { uint32_t v; asm volatile("ld.relaxed.gpu.global.u32 %0, [%1];" : "=r"(v) : "l"(p) : "memory"); return v; }
__device__ __forceinline__ float2 ld_relaxed_f2(const void* p) { float2 v; asm volatile("ld.relaxed.gpu.global.v2.f32 {%0,%1}, [%2];" : "=f"(v.x), "=f"(v.y) : "l"(p) : "memory"); return v; }
__device__ __forceinline__ float4 ld_relaxed_f4(const void* p) { float4 v; asm volatile("ld.relaxed.gpu.global.v4.f32 {%0,%1,%2,%3}, [%4];" : "=f"(v.x), "=f"(v.y), "=f"(v.z), "=f"(v.w) : "l"(p) : "memory"); return v; }
__device__ __forceinline__ void st_relaxed_b64(void* p, float a, uint32_t b) {
  asm volatile("{\n.reg .b64 v;\nmov.b64 v, {%1, %2};\nst.relaxed.gpu.global.b64 [%0], v;\n}" :: "l"(p), "r"(__float_as_uint(a)), "r"(b) : "memory");
}
__device__ __forceinline__ void red_add_u32(uint32_t* p, uint32_t v) { asm volatile("red.relaxed.gpu.global.add.u32 [%0], %1;" :: "l"(p), "r"(v) : "memory"); }
__device__ __forceinline__ void red_add_f2(float* p, float a, float b) { asm volatile("red.relaxed.gpu.global.add.v2.f32 [%0], {%1, %2};" :: "l"(p), "f"(a), "f"(b) : "memory"); }
__device__ __forceinline__ void red_add_f4(float* p, float a, float b, float c, float d) { asm volatile("red.relaxed.gpu.global.add.v4.f32 [%0], {%1, %2, %3, %4};" :: "l"(p), "f"(a), "f"(b), "f"(c), "f"(d) : "memory"); }
__device__ __forceinline__ void st_async_v4(uint32_t dst, uint32_t a, uint32_t b, uint32_t c, uint32_t d, uint32_t bar) {
  asm volatile("st.async.weak.shared::cluster.mbarrier::complete_tx::bytes.v4.b32 [%0], {%1,%2,%3,%4}, [%5];" :: "r"(dst), "r"(a), "r"(b), "r"(c), "r"(d), "r"(bar) : "memory");
}
__device__ __forceinline__ void stsm4(uint32_t addr, uint32_t a, uint32_t b, uint32_t c, uint32_t d) {
  asm volatile("stmatrix.sync.aligned.m8n8.x4.shared.b16 [%0], {%1,%2,%3,%4};" :: "r"(addr), "r"(a), "r"(b), "r"(c), "r"(d) : "memory");
}
__device__ __forceinline__ void ldsm4(uint32_t addr, uint32_t& a, uint32_t& b, uint32_t& c, uint32_t& d) {
  asm volatile("ldmatrix.sync.aligned.m8n8.x4.shared.b16 {%0,%1,%2,%3}, [%4];" : "=r"(a), "=r"(b), "=r"(c), "=r"(d) : "r"(addr) : "memory");
}
__device__ __forceinline__ void ldsm4t(uint32_t addr, uint32_t& a, uint32_t& b, uint32_t& c, uint32_t& d) {
  asm volatile("ldmatrix.sync.aligned.m8n8.x4.trans.shared.b16 {%0,%1,%2,%3}, [%4];" : "=r"(a), "=r"(b), "=r"(c), "=r"(d) : "r"(addr) : "memory");
}
__device__ __forceinline__ float2 lds_f2(uint32_t addr) { float2 v; asm volatile("ld.shared.v2.f32 {%0,%1}, [%2];" : "=f"(v.x), "=f"(v.y) : "r"(addr) : "memory"); return v; }
__device__ __forceinline__ uint32_t lds_u32(uint32_t addr) { uint32_t v; asm volatile("ld.shared.u32 %0, [%1];" : "=r"(v) : "r"(addr) : "memory"); return v; }
__device__ __forceinline__ void sts_u4(uint32_t addr, uint4 v) { asm volatile("st.shared.v4.u32 [%0], {%1,%2,%3,%4};" :: "r"(addr), "r"(v.x), "r"(v.y), "r"(v.z), "r"(v.w) : "memory"); }
__device__ __forceinline__ uint4 ld_relaxed_u4(const void* p) { uint4 v; asm volatile("ld.relaxed.gpu.global.v4.u32 {%0,%1,%2,%3}, [%4];" : "=r"(v.x), "=r"(v.y), "=r"(v.z), "=r"(v.w) : "l"(p) : "memory"); return v; }
__device__ __forceinline__ void st_relaxed_u32(uint32_t* p, uint32_t v) { asm volatile("st.relaxed.gpu.global.u32 [%0], %1;" :: "l"(p), "r"(v) : "memory"); }
__device__ __forceinline__ void st_relaxed_f4(void* p, float a, float b, float c, uint32_t d) { asm volatile("st.relaxed.gpu.global.v4.b32 [%0], {%1,%2,%3,%4};" :: "l"(p), "r"(__float_as_uint(a)), "r"(__float_as_uint(b)), "r"(__float_as_uint(c)), "r"(d) : "memory"); }
__device__ __forceinline__ uint2 lds_u2(uint32_t addr) { uint2 v; asm volatile("ld.shared.v2.u32 {%0,%1}, [%2];" : "=r"(v.x), "=r"(v.y) : "r"(addr) : "memory"); return v; }
__device__ __forceinline__ uint4 lds_u4(uint32_t addr) { uint4 v; asm volatile("ld.shared.v4.u32 {%0,%1,%2,%3}, [%4];" : "=r"(v.x), "=r"(v.y), "=r"(v.z), "=r"(v.w) : "r"(addr) : "memory"); return v; }
__device__ __forceinline__ void sts_f2(uint32_t addr, float a, float b) { asm volatile("st.shared.v2.f32 [%0], {%1,%2};" :: "r"(addr), "f"(a), "f"(b) : "memory"); }
__device__ __forceinline__ void sts_u2(uint32_t addr, uint32_t a, uint32_t b) { asm volatile("st.shared.v2.u32 [%0], {%1,%2};" :: "r"(addr), "r"(a), "r"(b) : "memory"); }
__device__ __forceinline__ void sts_f4(uint32_t addr, float4 v) { asm volatile("st.shared.v4.f32 [%0], {%1,%2,%3,%4};" :: "r"(addr), "f"(v.x), "f"(v.y), "f"(v.z), "f"(v.w) : "memory"); }
__device__ __forceinline__ void mma16816(float (&c)[4], uint32_t a0, uint32_t a1, uint32_t a2, uint32_t a3, uint32_t b0, uint32_t b1) {
  asm volatile("mma.sync.aligned.m16n8k16.row.col.f32.bf16.bf16.f32 {%0,%1,%2,%3}, {%4,%5,%6,%7}, {%8,%9}, {%0,%1,%2,%3};"
               : "+f"(c[0]), "+f"(c[1]), "+f"(c[2]), "+f"(c[3]) : "r"(a0), "r"(a1), "r"(a2), "r"(a3), "r"(b0), "r"(b1));
}
__device__ __forceinline__ uint32_t pack_bf16(float lo, float hi) { uint32_t r; asm("cvt.rn.bf16x2.f32 %0, %1, %2;" : "=r"(r) : "f"(hi), "f"(lo)); return r; }
__device__ __forceinline__ uint32_t pack_bf16_relu(float lo, float hi) { uint32_t r; asm("cvt.rn.relu.bf16x2.f32 %0, %1, %2;" : "=r"(r) : "f"(hi), "f"(lo)); return r; }
__device__ __forceinline__ float bf_lo(uint32_t v) { return __uint_as_float(v << 16); }
__device__ __forceinline__ float bf_hi(uint32_t v) { return __uint_as_float(v & 0xffff0000u); }
__device__ __forceinline__ float ex2(float x) { float y; asm("ex2.approx.ftz.f32 %0, %1;" : "=f"(y) : "f"(x)); return y; }
__device__ __forceinline__ float rcp(float x) { float y; asm("rcp.approx.ftz.f32 %0, %1;" : "=f"(y) : "f"(x)); return y; }
__device__ __forceinline__ float phi_y(float y) { return fmaf(fmaxf(y, 1.4426950408889634e-6f), 0.6931471805599453f, ex2(fminf(y, 0.f))); }
__device__ __forceinline__ int opaque(int x) { int y; asm volatile("mov.u32 %0, %1;" : "=r"(y) : "r"(x)); return y; }
__device__ __forceinline__ void wg_fence() { asm volatile("wgmma.fence.sync.aligned;" ::: "memory"); }
__device__ __forceinline__ void wg_fence_in() { if (!NOFENCE) wg_fence(); }
__device__ __forceinline__ void wg_commit() { asm volatile("wgmma.commit_group.sync.aligned;" ::: "memory"); }
template <int N> __device__ __forceinline__ void wg_wait() { asm volatile("wgmma.wait_group.sync.aligned %0;" :: "n"(N) : "memory"); }
template <int N> __device__ __forceinline__ void fence_regs(float (&d)[N]) {
#pragma unroll
  for (int i = 0; i < N; i++) asm volatile("" : "+f"(d[i]) :: "memory");
}
template <int N> __device__ __forceinline__ void zero_regs(float (&d)[N]) {
#pragma unroll
  for (int i = 0; i < N; i++) d[i] = 0.f;
  fence_regs(d);
}
__device__ __forceinline__ void wg_bar(int wg) { if (wg == 0) asm volatile("bar.sync 1, 128;" ::: "memory"); else asm volatile("bar.sync 2, 128;" ::: "memory"); }
__device__ __forceinline__ uint32_t desc_lo(uint32_t addr, uint32_t lbo) { return ((addr & 0x3FFFF) >> 4) | ((lbo >> 4) << 16); }
constexpr uint32_t HI_SW = 0x40000040u;
constexpr uint32_t HI_NS = 0x00000008u;
template <int I> struct IC { static constexpr int value = I; };
template <int B, int E, class F> __device__ __forceinline__ void static_for(F&& f) {
  if constexpr (B < E) { f(IC<B>{}); static_for<B + 1, E>(f); }
}

template <int OA, int OB, uint32_t HA>
__device__ __forceinline__ void wgmma_n64_init(float (&d)[32], uint32_t la, uint32_t lb) {
  asm volatile("{\n.reg .pred p;\n.reg .b32 ta, tb;\n.reg .b64 da, db;\n"
    "setp.ne.b32 p, 0, 0;\nadd.u32 ta, %32, %34;\nadd.u32 tb, %33, %35;\n"
    "mov.b64 da, {ta, %36};\nmov.b64 db, {tb, 0x40000040};\n"
    "wgmma.mma_async.sync.aligned.m64n64k16.f32.bf16.bf16 "
    "{%0, %1, %2, %3, %4, %5, %6, %7, %8, %9, %10, %11, %12, %13, %14, %15, "
    "%16, %17, %18, %19, %20, %21, %22, %23, %24, %25, %26, %27, %28, %29, %30, %31}, "
    "da, db, p, 1, 1, 0, 1;\n}"
    : "=f"(d[0]), "=f"(d[1]), "=f"(d[2]), "=f"(d[3]), "=f"(d[4]), "=f"(d[5]), "=f"(d[6]), "=f"(d[7]),
      "=f"(d[8]), "=f"(d[9]), "=f"(d[10]), "=f"(d[11]), "=f"(d[12]), "=f"(d[13]), "=f"(d[14]), "=f"(d[15]),
      "=f"(d[16]), "=f"(d[17]), "=f"(d[18]), "=f"(d[19]), "=f"(d[20]), "=f"(d[21]), "=f"(d[22]), "=f"(d[23]),
      "=f"(d[24]), "=f"(d[25]), "=f"(d[26]), "=f"(d[27]), "=f"(d[28]), "=f"(d[29]), "=f"(d[30]), "=f"(d[31])
    : "r"(la), "r"(lb), "n"(OA), "n"(OB), "n"(HA));
}
template <int OA, int OB, uint32_t HA>
__device__ __forceinline__ void wgmma_n128_init(float (&d)[32], float (&e)[32], uint32_t la, uint32_t lb) {
  asm volatile("{\n.reg .pred p;\n.reg .b32 ta, tb;\n.reg .b64 da, db;\n"
    "setp.ne.b32 p, 0, 0;\nadd.u32 ta, %64, %66;\nadd.u32 tb, %65, %67;\n"
    "mov.b64 da, {ta, %68};\nmov.b64 db, {tb, 0x40000040};\n"
    "wgmma.mma_async.sync.aligned.m64n128k16.f32.bf16.bf16 "
    "{%0, %1, %2, %3, %4, %5, %6, %7, %8, %9, %10, %11, %12, %13, %14, %15, "
    "%16, %17, %18, %19, %20, %21, %22, %23, %24, %25, %26, %27, %28, %29, %30, %31, "
    "%32, %33, %34, %35, %36, %37, %38, %39, %40, %41, %42, %43, %44, %45, %46, %47, "
    "%48, %49, %50, %51, %52, %53, %54, %55, %56, %57, %58, %59, %60, %61, %62, %63}, "
    "da, db, p, 1, 1, 0, 1;\n}"
    : "=f"(d[0]), "=f"(d[1]), "=f"(d[2]), "=f"(d[3]), "=f"(d[4]), "=f"(d[5]), "=f"(d[6]), "=f"(d[7]),
      "=f"(d[8]), "=f"(d[9]), "=f"(d[10]), "=f"(d[11]), "=f"(d[12]), "=f"(d[13]), "=f"(d[14]), "=f"(d[15]),
      "=f"(d[16]), "=f"(d[17]), "=f"(d[18]), "=f"(d[19]), "=f"(d[20]), "=f"(d[21]), "=f"(d[22]), "=f"(d[23]),
      "=f"(d[24]), "=f"(d[25]), "=f"(d[26]), "=f"(d[27]), "=f"(d[28]), "=f"(d[29]), "=f"(d[30]), "=f"(d[31]),
      "=f"(e[0]), "=f"(e[1]), "=f"(e[2]), "=f"(e[3]), "=f"(e[4]), "=f"(e[5]), "=f"(e[6]), "=f"(e[7]),
      "=f"(e[8]), "=f"(e[9]), "=f"(e[10]), "=f"(e[11]), "=f"(e[12]), "=f"(e[13]), "=f"(e[14]), "=f"(e[15]),
      "=f"(e[16]), "=f"(e[17]), "=f"(e[18]), "=f"(e[19]), "=f"(e[20]), "=f"(e[21]), "=f"(e[22]), "=f"(e[23]),
      "=f"(e[24]), "=f"(e[25]), "=f"(e[26]), "=f"(e[27]), "=f"(e[28]), "=f"(e[29]), "=f"(e[30]), "=f"(e[31])
    : "r"(la), "r"(lb), "n"(OA), "n"(OB), "n"(HA));
}
template <int OA, int OB, uint32_t HA>
__device__ __forceinline__ void wgmma_n176_init(float (&d)[88], uint32_t la, uint32_t lb) {
  asm volatile("{\n.reg .pred p;\n.reg .b32 ta, tb;\n.reg .b64 da, db;\n"
    "setp.ne.b32 p, 0, 0;\nadd.u32 ta, %88, %90;\nadd.u32 tb, %89, %91;\n"
    "mov.b64 da, {ta, %92};\nmov.b64 db, {tb, 0x40000040};\n"
    "wgmma.mma_async.sync.aligned.m64n176k16.f32.bf16.bf16 "
    "{%0, %1, %2, %3, %4, %5, %6, %7, %8, %9, %10, %11, %12, %13, %14, %15, "
    "%16, %17, %18, %19, %20, %21, %22, %23, %24, %25, %26, %27, %28, %29, %30, %31, "
    "%32, %33, %34, %35, %36, %37, %38, %39, %40, %41, %42, %43, %44, %45, %46, %47, "
    "%48, %49, %50, %51, %52, %53, %54, %55, %56, %57, %58, %59, %60, %61, %62, %63, "
    "%64, %65, %66, %67, %68, %69, %70, %71, %72, %73, %74, %75, %76, %77, %78, %79, "
    "%80, %81, %82, %83, %84, %85, %86, %87}, "
    "da, db, p, 1, 1, 0, 1;\n}"
    : "=f"(d[0]), "=f"(d[1]), "=f"(d[2]), "=f"(d[3]), "=f"(d[4]), "=f"(d[5]), "=f"(d[6]), "=f"(d[7]),
      "=f"(d[8]), "=f"(d[9]), "=f"(d[10]), "=f"(d[11]), "=f"(d[12]), "=f"(d[13]), "=f"(d[14]), "=f"(d[15]),
      "=f"(d[16]), "=f"(d[17]), "=f"(d[18]), "=f"(d[19]), "=f"(d[20]), "=f"(d[21]), "=f"(d[22]), "=f"(d[23]),
      "=f"(d[24]), "=f"(d[25]), "=f"(d[26]), "=f"(d[27]), "=f"(d[28]), "=f"(d[29]), "=f"(d[30]), "=f"(d[31]),
      "=f"(d[32]), "=f"(d[33]), "=f"(d[34]), "=f"(d[35]), "=f"(d[36]), "=f"(d[37]), "=f"(d[38]), "=f"(d[39]),
      "=f"(d[40]), "=f"(d[41]), "=f"(d[42]), "=f"(d[43]), "=f"(d[44]), "=f"(d[45]), "=f"(d[46]), "=f"(d[47]),
      "=f"(d[48]), "=f"(d[49]), "=f"(d[50]), "=f"(d[51]), "=f"(d[52]), "=f"(d[53]), "=f"(d[54]), "=f"(d[55]),
      "=f"(d[56]), "=f"(d[57]), "=f"(d[58]), "=f"(d[59]), "=f"(d[60]), "=f"(d[61]), "=f"(d[62]), "=f"(d[63]),
      "=f"(d[64]), "=f"(d[65]), "=f"(d[66]), "=f"(d[67]), "=f"(d[68]), "=f"(d[69]), "=f"(d[70]), "=f"(d[71]),
      "=f"(d[72]), "=f"(d[73]), "=f"(d[74]), "=f"(d[75]), "=f"(d[76]), "=f"(d[77]), "=f"(d[78]), "=f"(d[79]),
      "=f"(d[80]), "=f"(d[81]), "=f"(d[82]), "=f"(d[83]), "=f"(d[84]), "=f"(d[85]), "=f"(d[86]), "=f"(d[87])
    : "r"(la), "r"(lb), "n"(OA), "n"(OB), "n"(HA));
}
template <int OA, int OB, uint32_t HA>
__device__ __forceinline__ void wgmma_n64(float (&d)[32], uint32_t la, uint32_t lb) {
  asm volatile("{\n.reg .pred p;\n.reg .b32 ta, tb;\n.reg .b64 da, db;\n"
    "setp.eq.b32 p, 0, 0;\nadd.u32 ta, %32, %34;\nadd.u32 tb, %33, %35;\n"
    "mov.b64 da, {ta, %36};\nmov.b64 db, {tb, 0x40000040};\n"
    "wgmma.mma_async.sync.aligned.m64n64k16.f32.bf16.bf16 "
    "{%0, %1, %2, %3, %4, %5, %6, %7, %8, %9, %10, %11, %12, %13, %14, %15, "
    "%16, %17, %18, %19, %20, %21, %22, %23, %24, %25, %26, %27, %28, %29, %30, %31}, "
    "da, db, p, 1, 1, 0, 1;\n}"
    : "+f"(d[0]), "+f"(d[1]), "+f"(d[2]), "+f"(d[3]), "+f"(d[4]), "+f"(d[5]), "+f"(d[6]), "+f"(d[7]),
      "+f"(d[8]), "+f"(d[9]), "+f"(d[10]), "+f"(d[11]), "+f"(d[12]), "+f"(d[13]), "+f"(d[14]), "+f"(d[15]),
      "+f"(d[16]), "+f"(d[17]), "+f"(d[18]), "+f"(d[19]), "+f"(d[20]), "+f"(d[21]), "+f"(d[22]), "+f"(d[23]),
      "+f"(d[24]), "+f"(d[25]), "+f"(d[26]), "+f"(d[27]), "+f"(d[28]), "+f"(d[29]), "+f"(d[30]), "+f"(d[31])
    : "r"(la), "r"(lb), "n"(OA), "n"(OB), "n"(HA));
}
template <int OA, int OB, uint32_t HA>
__device__ __forceinline__ void wgmma_n128(float (&d)[32], float (&e)[32], uint32_t la, uint32_t lb) {
  asm volatile("{\n.reg .pred p;\n.reg .b32 ta, tb;\n.reg .b64 da, db;\n"
    "setp.eq.b32 p, 0, 0;\nadd.u32 ta, %64, %66;\nadd.u32 tb, %65, %67;\n"
    "mov.b64 da, {ta, %68};\nmov.b64 db, {tb, 0x40000040};\n"
    "wgmma.mma_async.sync.aligned.m64n128k16.f32.bf16.bf16 "
    "{%0, %1, %2, %3, %4, %5, %6, %7, %8, %9, %10, %11, %12, %13, %14, %15, "
    "%16, %17, %18, %19, %20, %21, %22, %23, %24, %25, %26, %27, %28, %29, %30, %31, "
    "%32, %33, %34, %35, %36, %37, %38, %39, %40, %41, %42, %43, %44, %45, %46, %47, "
    "%48, %49, %50, %51, %52, %53, %54, %55, %56, %57, %58, %59, %60, %61, %62, %63}, "
    "da, db, p, 1, 1, 0, 1;\n}"
    : "+f"(d[0]), "+f"(d[1]), "+f"(d[2]), "+f"(d[3]), "+f"(d[4]), "+f"(d[5]), "+f"(d[6]), "+f"(d[7]),
      "+f"(d[8]), "+f"(d[9]), "+f"(d[10]), "+f"(d[11]), "+f"(d[12]), "+f"(d[13]), "+f"(d[14]), "+f"(d[15]),
      "+f"(d[16]), "+f"(d[17]), "+f"(d[18]), "+f"(d[19]), "+f"(d[20]), "+f"(d[21]), "+f"(d[22]), "+f"(d[23]),
      "+f"(d[24]), "+f"(d[25]), "+f"(d[26]), "+f"(d[27]), "+f"(d[28]), "+f"(d[29]), "+f"(d[30]), "+f"(d[31]),
      "+f"(e[0]), "+f"(e[1]), "+f"(e[2]), "+f"(e[3]), "+f"(e[4]), "+f"(e[5]), "+f"(e[6]), "+f"(e[7]),
      "+f"(e[8]), "+f"(e[9]), "+f"(e[10]), "+f"(e[11]), "+f"(e[12]), "+f"(e[13]), "+f"(e[14]), "+f"(e[15]),
      "+f"(e[16]), "+f"(e[17]), "+f"(e[18]), "+f"(e[19]), "+f"(e[20]), "+f"(e[21]), "+f"(e[22]), "+f"(e[23]),
      "+f"(e[24]), "+f"(e[25]), "+f"(e[26]), "+f"(e[27]), "+f"(e[28]), "+f"(e[29]), "+f"(e[30]), "+f"(e[31])
    : "r"(la), "r"(lb), "n"(OA), "n"(OB), "n"(HA));
}
template <int OA, int OB, uint32_t HA>
__device__ __forceinline__ void wgmma_n176(float (&d)[88], uint32_t la, uint32_t lb) {
  asm volatile("{\n.reg .pred p;\n.reg .b32 ta, tb;\n.reg .b64 da, db;\n"
    "setp.eq.b32 p, 0, 0;\nadd.u32 ta, %88, %90;\nadd.u32 tb, %89, %91;\n"
    "mov.b64 da, {ta, %92};\nmov.b64 db, {tb, 0x40000040};\n"
    "wgmma.mma_async.sync.aligned.m64n176k16.f32.bf16.bf16 "
    "{%0, %1, %2, %3, %4, %5, %6, %7, %8, %9, %10, %11, %12, %13, %14, %15, "
    "%16, %17, %18, %19, %20, %21, %22, %23, %24, %25, %26, %27, %28, %29, %30, %31, "
    "%32, %33, %34, %35, %36, %37, %38, %39, %40, %41, %42, %43, %44, %45, %46, %47, "
    "%48, %49, %50, %51, %52, %53, %54, %55, %56, %57, %58, %59, %60, %61, %62, %63, "
    "%64, %65, %66, %67, %68, %69, %70, %71, %72, %73, %74, %75, %76, %77, %78, %79, "
    "%80, %81, %82, %83, %84, %85, %86, %87}, "
    "da, db, p, 1, 1, 0, 1;\n}"
    : "+f"(d[0]), "+f"(d[1]), "+f"(d[2]), "+f"(d[3]), "+f"(d[4]), "+f"(d[5]), "+f"(d[6]), "+f"(d[7]),
      "+f"(d[8]), "+f"(d[9]), "+f"(d[10]), "+f"(d[11]), "+f"(d[12]), "+f"(d[13]), "+f"(d[14]), "+f"(d[15]),
      "+f"(d[16]), "+f"(d[17]), "+f"(d[18]), "+f"(d[19]), "+f"(d[20]), "+f"(d[21]), "+f"(d[22]), "+f"(d[23]),
      "+f"(d[24]), "+f"(d[25]), "+f"(d[26]), "+f"(d[27]), "+f"(d[28]), "+f"(d[29]), "+f"(d[30]), "+f"(d[31]),
      "+f"(d[32]), "+f"(d[33]), "+f"(d[34]), "+f"(d[35]), "+f"(d[36]), "+f"(d[37]), "+f"(d[38]), "+f"(d[39]),
      "+f"(d[40]), "+f"(d[41]), "+f"(d[42]), "+f"(d[43]), "+f"(d[44]), "+f"(d[45]), "+f"(d[46]), "+f"(d[47]),
      "+f"(d[48]), "+f"(d[49]), "+f"(d[50]), "+f"(d[51]), "+f"(d[52]), "+f"(d[53]), "+f"(d[54]), "+f"(d[55]),
      "+f"(d[56]), "+f"(d[57]), "+f"(d[58]), "+f"(d[59]), "+f"(d[60]), "+f"(d[61]), "+f"(d[62]), "+f"(d[63]),
      "+f"(d[64]), "+f"(d[65]), "+f"(d[66]), "+f"(d[67]), "+f"(d[68]), "+f"(d[69]), "+f"(d[70]), "+f"(d[71]),
      "+f"(d[72]), "+f"(d[73]), "+f"(d[74]), "+f"(d[75]), "+f"(d[76]), "+f"(d[77]), "+f"(d[78]), "+f"(d[79]),
      "+f"(d[80]), "+f"(d[81]), "+f"(d[82]), "+f"(d[83]), "+f"(d[84]), "+f"(d[85]), "+f"(d[86]), "+f"(d[87])
    : "r"(la), "r"(lb), "n"(OA), "n"(OB), "n"(HA));
}

__device__ __forceinline__ void publish_stats(const uint32_t (&xr)[16], float2* dst  , int t, uint32_t tag) {
  float s0 = 0.f, s1 = 0.f;
#pragma unroll
  for (int j = 0; j < 8; j++) { s0 += bf_lo(xr[2 * j]) + bf_hi(xr[2 * j]); s1 += bf_lo(xr[2 * j + 1]) + bf_hi(xr[2 * j + 1]); }
  s0 += __shfl_xor_sync(0xffffffff, s0, 1); s1 += __shfl_xor_sync(0xffffffff, s1, 1);
  s0 += __shfl_xor_sync(0xffffffff, s0, 2); s1 += __shfl_xor_sync(0xffffffff, s1, 2);
  const float m0 = s0 * (1.f / 64.f), m1 = s1 * (1.f / 64.f);
  float q0 = 0.f, q1 = 0.f;
#pragma unroll
  for (int j = 0; j < 8; j++) {
    float a = bf_lo(xr[2 * j]) - m0, b = bf_hi(xr[2 * j]) - m0, c = bf_lo(xr[2 * j + 1]) - m1, d = bf_hi(xr[2 * j + 1]) - m1;
    q0 = fmaf(a, a, q0); q0 = fmaf(b, b, q0); q1 = fmaf(c, c, q1); q1 = fmaf(d, d, q1);
  }
  q0 += __shfl_xor_sync(0xffffffff, q0, 1); q1 += __shfl_xor_sync(0xffffffff, q1, 1);
  q0 += __shfl_xor_sync(0xffffffff, q0, 2); q1 += __shfl_xor_sync(0xffffffff, q1, 2);
  if (t < 2) st_relaxed_b64(dst + 8 * t, t ? s1 : s0, (__float_as_uint(t ? q1 : q0) & ~1u) | tag);
}

__device__ __forceinline__ void gather_stats(const float2* src  , uint32_t sm_dst, uint32_t bar, int lane, uint32_t tag) {
  const float2* p = src + lane * 2;
  float4 v[8];
  uint32_t cnt = 0;
  while (true) {
#pragma unroll
    for (int i = 0; i < 8; i++) v[i] = ld_relaxed_f4(p + i * 64);
    uint32_t bad = 0;
#pragma unroll
    for (int i = 0; i < 8; i++) bad |= (__float_as_uint(v[i].y) ^ tag) | (__float_as_uint(v[i].w) ^ tag);
    if (__all_sync(0xffffffff, (bad & 1u) == 0)) break;
    if (++cnt > SPIN_LIMIT) __trap();
    __nanosleep(100);
  }
  float sa = 0.f, sb = 0.f, qa = 0.f, qb = 0.f;
#pragma unroll
  for (int i = 0; i < 8; i++) { sa += v[i].x; qa += v[i].y; sb += v[i].z; qb += v[i].w; }
  const float ma = sa * (1.f / 512.f), mb = sb * (1.f / 512.f);
  float da = 0.f, db = 0.f;
#pragma unroll
  for (int i = 0; i < 8; i++) {
    const float a = v[i].x * (1.f / 64.f) - ma, b = v[i].z * (1.f / 64.f) - mb;
    da = fmaf(a, a, da); db = fmaf(b, b, db);
  }
  sts_f4(sm_dst + lane * 16, make_float4(rsqrtf(fmaf(da, 64.f, qa) * (1.f / 512.f) + 1e-5f), -ma, rsqrtf(fmaf(db, 64.f, qb) * (1.f / 512.f) + 1e-5f), -mb));
  __syncwarp();
  if (lane == 0) mbar_arrive(bar);
}

__device__ __forceinline__ void colsum_task(const __nv_bfloat16* p  , int pitch, bool ok, int row0, float4* dst  , int lane, uint32_t tag) {
  const int rg = lane >> 3;
  float a[8];
#pragma unroll
  for (int i = 0; i < 8; i++) a[i] = 0.f;
  if (ok) {
    uint4 v[8];
#pragma unroll
    for (int i = 0; i < 8; i++) v[i] = __ldg((const uint4*)(p + (size_t)(row0 + 4 * i + rg) * pitch));
#pragma unroll
    for (int i = 0; i < 8; i++) {
      a[0] += bf_lo(v[i].x); a[1] += bf_hi(v[i].x); a[2] += bf_lo(v[i].y); a[3] += bf_hi(v[i].y);
      a[4] += bf_lo(v[i].z); a[5] += bf_hi(v[i].z); a[6] += bf_lo(v[i].w); a[7] += bf_hi(v[i].w);
    }
  }
#pragma unroll
  for (int i = 0; i < 8; i++) { a[i] += __shfl_xor_sync(0xffffffff, a[i], 8); a[i] += __shfl_xor_sync(0xffffffff, a[i], 16); }
  if (rg == 0) {
    st_relaxed_f4(dst, a[0], a[1], a[2], (__float_as_uint(a[3]) & ~1u) | tag);
    st_relaxed_f4(dst + 1, a[4], a[5], a[6], (__float_as_uint(a[7]) & ~1u) | tag);
  }
}
__device__ __forceinline__ void colsum_gather(const float4* src, uint32_t sm_dst, int nunits, int lane, uint32_t tag) {
#pragma unroll 1
  for (int j = 0; j < 3; j++) {
    const float4* p = src + (lane >> 4) * 8 * 48 + j * 16 + (lane & 15);
    float4 v[8];
    uint32_t cnt = 0;
    while (true) {
      uint32_t bad = 0;
#pragma unroll
      for (int i = 0; i < 8; i++) v[i] = ld_relaxed_f4(p + i * 48);
#pragma unroll
      for (int i = 0; i < 8; i++) bad |= __float_as_uint(v[i].w) ^ tag;
      if (__all_sync(0xffffffff, (bad & 1u) == 0)) break;
      if (++cnt > SPIN_LIMIT) __trap();
    }
    float4 a = v[0];
#pragma unroll
    for (int i = 1; i < 8; i++) { a.x += v[i].x; a.y += v[i].y; a.z += v[i].z; a.w += v[i].w; }
    a.x += __shfl_xor_sync(0xffffffff, a.x, 16); a.y += __shfl_xor_sync(0xffffffff, a.y, 16);
    a.z += __shfl_xor_sync(0xffffffff, a.z, 16); a.w += __shfl_xor_sync(0xffffffff, a.w, 16);
    if (lane < 16 && j * 16 + lane < nunits) sts_f4(sm_dst + (j * 16 + lane) * 16, a);
  }
  __syncwarp();
}

__device__ __forceinline__ void wait_flag_acq(const uint32_t* f, uint32_t ev) {
  uint32_t cnt = 0;
  while ((int32_t)(ld_acquire(f) - ev) < 0) { if (++cnt > SPIN_LIMIT) __trap(); }
}
__device__ __forceinline__ void wait_flags(const uint32_t* f  , uint32_t ev) {
  uint32_t cnt = 0;
  while (!__all_sync(0xffffffff, (int32_t)(ld_relaxed(f) - ev) >= 0)) { if (++cnt > SPIN_LIMIT) __trap(); }
}
__device__ __forceinline__ void set_flags(uint4* flag  , uint32_t ev, int lane) {
  if (lane < 16) asm volatile("st.relaxed.gpu.global.v4.u32 [%0], {%1,%1,%1,%1};" :: "l"(flag + (lane >> 1) * 16 + (lane & 1)), "r"(ev) : "memory");
}
__device__ __forceinline__ void publish_chunk(uint4* gdst, uint32_t src, uint4* flag, uint32_t ev, int lane) {
  if (lane == 0) { bulk_s2g(gdst, src, 8192); bulk_commit(); PUBWAIT<0>(); }
  __syncwarp();
  set_flags(flag, ev, lane);
}
template <int N, int STR>
__device__ __forceinline__ void fetch_chunks(const uint4* gbuf  , const uint4* flags, uint32_t abase, uint32_t afull, int r, uint32_t ev, int lane) {
  const uint32_t* f = (const uint32_t*)(flags + r * 16 + ((r + STR * lane) & 7) * 2);
  uint32_t todo = (1u << N) - 2, cnt = 0;
  while (todo) {
    const uint32_t rdy = __ballot_sync(0xffffffff, (int32_t)(ld_relaxed(f) - ev) >= 0) & todo;
#pragma unroll
    for (int i = 1; i < N; i++) {
      if ((rdy >> i) & 1) {
        if (elect_one()) {
          mbar_expect_tx(afull + i * 8, 8192);
          bulk_g2s(abase + i * 8192, gbuf + ((r + STR * i) & 7) * 512, 8192, afull + i * 8);
        }
      }
    }
    todo &= ~rdy;
    if (++cnt > SPIN_LIMIT) __trap();
  }
  __syncwarp();
}

__global__ void __cluster_dims__(2, 1, 1) __launch_bounds__(384, 1)
fused_kernel(const __grid_constant__ CUtensorMap tm_x, const __grid_constant__ CUtensorMap tm_out,
             const __grid_constant__ CUtensorMap tm_wqkv, const __grid_constant__ CUtensorMap tm_wo,
             const __grid_constant__ CUtensorMap tm_w1, const __grid_constant__ CUtensorMap tm_w2, const __grid_constant__ CUtensorMap tm_w2s,
             const __nv_bfloat16* __restrict__ wqkv, const __nv_bfloat16* __restrict__ wo,
             const __nv_bfloat16* __restrict__ w1, const __nv_bfloat16* __restrict__ w2) {
  extern __shared__ __align__(1024) uint8_t smem_raw[];
  const uint32_t sb = smem_u32(smem_raw);
  const int warp = __shfl_sync(0xffffffff, threadIdx.x >> 5, 0);
  const int bid = __shfl_sync(0xffffffff, opaque(blockIdx.x), 0);
  int cb, r;
  {
    const int cl = bid >> 1;
    cb = cl >> 2; r = (cl & 3) * 2 + (bid & 1);
  }

  const int prof_id = cb * 8 + r; (void)prof_id;
  if (threadIdx.x == 0) {
    if (sb & 1023) __trap();
    for (int i = 0; i < 4; i++) { mbar_init(sb + B_BFULL + i * 8, 1); mbar_init(sb + B_BEMPTY + i * 8, 8); }
    for (int i = 0; i < 16; i++) mbar_init(sb + B_AFULL + i * 8, 1);
    for (int i = 0; i < 6; i++) { mbar_init(sb + B_AFREE + i * 8, 4); mbar_init(sb + B_OWN + i * 8, 4); }
    for (int i = 0; i < 2; i++) { mbar_init(sb + B_STAT + i * 8, 1); mbar_init(sb + B_PRDY + i * 8, 1); mbar_init(sb + B_PFREE + i * 8, 4); }
    mbar_init(sb + B_CSRDY, 1); mbar_init(sb + B_CSRDY + 8, 1); mbar_init(sb + B_KVDONE, 4); mbar_init(sb + B_KVRDY, 1);
    asm volatile("fence.mbarrier_init.release.cluster;" ::: "memory");
  }
  __syncthreads();
  asm volatile("barrier.cluster.arrive.relaxed.aligned;" ::: "memory");

  if (warp >= 8) {
  asm volatile("setmaxnreg.dec.sync.aligned.u32 96;");
  const int lane = __shfl_sync(0xffffffff, threadIdx.x & 31, threadIdx.x & 31);
  const uint32_t epoch = ld_relaxed(g_epoch + bid * 8);
  if (warp == 8) {
    uint32_t st = 0;
    auto acquire = [&](uint32_t bytes) -> uint32_t {
      const uint32_t s = st & 3;
      mbar_wait(sb + B_BEMPTY + s * 8, ((st >> 2) & 1) ^ 1);
      st++;
      return s;
    };
    if (lane == 0) { prefetch_map(&tm_wqkv); prefetch_map(&tm_wo); prefetch_map(&tm_w1); prefetch_map(&tm_w2); prefetch_map(&tm_w2s); }
#pragma unroll 1
    for (int l = 0; l < 2; l++) {
#pragma unroll 1
      for (int i = 0; i < 8; i++) {
        const uint32_t s = acquire(0), dst = sb + SM_RING + s * SLOT, fb = sb + B_BFULL + s * 8;
        const int kc = (r + i) & 7;
        if (elect_one()) { mbar_expect_tx(fb, 16384); tma_load(dst, &tm_wqkv, 512 + 64 * r, 64 * kc, fb); tma_load(dst + 8192, &tm_wqkv, 1024 + 64 * r, 64 * kc, fb); }
      }
#pragma unroll 1
      for (int i = 0; i < 4; i++) {
        const uint32_t s = acquire(0), dst = sb + SM_RING + s * SLOT, fb = sb + B_BFULL + s * 8;
        if (elect_one()) { mbar_expect_tx(fb, 16384); tma_load(dst, &tm_wqkv, 64 * r, 64 * ((r + 2 * i) & 7), fb); tma_load(dst + 8192, &tm_wqkv, 64 * r, 64 * ((r + 2 * i + 1) & 7), fb); }
      }
#pragma unroll 1
      for (int i = 0; i < 4; i++) {
        const uint32_t s = acquire(0), dst = sb + SM_RING + s * SLOT, fb = sb + B_BFULL + s * 8;
        const int row = 64 * ((r + 2 * i) & 7);
        if (elect_one()) { mbar_expect_tx(fb, 16384); tma_load(dst, &tm_wo, 64 * (r ^ 1), row, fb); tma_load(dst + 8192, &tm_wo, 64 * r, row, fb); }
      }
#pragma unroll 1
      for (int i = 0; i < 8; i++) {
        const uint32_t s = acquire(0), dst = sb + SM_RING + s * SLOT, fb = sb + B_BFULL + s * 8;
        const int kc = (r + i) & 7;
        if (elect_one()) { mbar_expect_tx(fb, 24576); tma_load(dst, &tm_w1, kHS * r, 64 * kc, fb); tma_load(dst + 8192, &tm_w1, kHS * r + 64, 64 * kc, fb); tma_load(dst + 16384, &tm_w1, kHS * r + 128, 64 * kc, fb); }
      }
#pragma unroll 1
      for (int i = 0; i < 8; i++) {
        const uint32_t s = acquire(0), dst = sb + SM_RING + s * SLOT, fb = sb + B_BFULL + s * 8;
        const int t = i < 2 ? 0 : i < 5 ? i - 1 : i - 4, bb = i < 2 ? i : i >= 5;
        const int row = kHS * ((r + 2 * t) & 7) + 96 * bb;
        if (elect_one()) {
          const CUtensorMap* m = bb ? &tm_w2s : &tm_w2;
          mbar_expect_tx(fb, bb ? 20480 : 24576); tma_load(dst, m, 64 * (r ^ 1), row, fb); tma_load(dst + 12288, m, 64 * r, row, fb);
        }
      }
    }
    asm volatile("barrier.cluster.wait.aligned;" ::: "memory");
  } else if (warp == 9 || warp == 10) {
    const int h = warp - 9, half0 = cb * 2 + h;
    if (elect_one()) {
      const uint32_t abase = sb + h * 65536, afull = sb + B_AFULL + h * 64;
      prefetch_map(&tm_x);
      for (int i = 0; i < 8; i++) { mbar_expect_tx(afull + i * 8, 8192); tma_load(abase + i * 8192, &tm_x, 64 * ((r + i) & 7), 128 * cb + 64 * h, afull + i * 8); }
    }
    __syncwarp();
    const uint32_t ev0 = epoch * 16, tag = (epoch + 1) & 1;
    set_flags(g_flags + half0 * 128 + r * 2, ev0, lane);
    colsum_task(wqkv + (1 + h) * 512 + 64 * r + 8 * (lane & 7), 3 * kD, true, 32 * cb, g_cs + ((r * 2 + 0) * 16 + cb) * 48 + (1 + h) * 16 + 2 * (lane & 7), lane, tag);
    gather_stats(g_stats + (0 * 32 + half0) * 512, sb + SM_STAT + h * 512, sb + B_STAT + h * 8, lane, tag);
#pragma unroll 1
    for (int b = h; b < 3; b += 2) {
      const int col = 64 * b + 8 * (lane & 7);
      colsum_task(w1 + kHS * r + col, kFF, col < kHS && kHS * r + col < kFF, 32 * cb, g_cs + ((r * 2 + 1) * 16 + cb) * 48 + b * 16 + 2 * (lane & 7), lane, tag);
    }
    asm volatile("barrier.cluster.wait.aligned;" ::: "memory");
    uint32_t p0 = 0;
#pragma unroll 1
    for (int l = 0; l < 2; l++) {
      const uint32_t ev = ev0 + l * 6;
      const int half = opaque(half0);
      const uint32_t abase = sb + h * 65536, afull = sb + B_AFULL + h * 64, afree = sb + B_AFREE + h * 24, own = sb + B_OWN + h * 24;
      uint4* flags = g_flags + half * 128;
      mbar_wait(own, p0);
      STAMP(2 + h, l * 16 + 0);
      publish_chunk(g_act + (0 * 32 + half) * 4096 + r * 512, abase, flags + r * 2, ev + 1, lane);
      STAMP(2 + h, l * 16 + 11);
      mbar_wait(afree, p0); p0 ^= 1;
      fetch_chunks<4, 2>(g_act + (0 * 32 + half) * 4096, flags, abase, afull, r, ev + 1, lane);
      STAMP(2 + h, l * 16 + 1);
      mbar_wait(own, p0);
      STAMP(2 + h, l * 16 + 2);
      publish_chunk(g_act + (1 * 32 + half) * 4096 + r * 512, abase, flags + r * 2, ev + 2, lane);
      mbar_wait(afree, p0); p0 ^= 1;
      STAMP(2 + h, l * 16 + 12);
      fetch_chunks<8, 1>(g_act + (1 * 32 + half) * 4096, flags, abase, afull, r, ev + 2, lane);
      STAMP(2 + h, l * 16 + 4);
      gather_stats(g_stats + ((2 * l + 1) * 32 + half) * 512, sb + SM_STAT + h * 512, sb + B_STAT + h * 8, lane, tag);
      STAMP(2 + h, l * 16 + 3);
      uint4* hb = g_h + half * 8 * 1536;
      mbar_wait(afree, p0);
      mbar_wait(own, p0); p0 ^= 1;
      STAMP(2 + h, l * 16 + 5);
      if (lane == 0) { bulk_s2g(hb + r * 1536, abase, 12288); bulk_commit(); }
      mbar_wait(own + 8, l);
      if (lane == 0) { bulk_s2g(hb + r * 1536 + 768, abase + 12288, 10240); bulk_commit(); PUBWAIT<1>(); }
      __syncwarp();
      set_flags(flags + r * 2, ev + 3, lane);
      STAMP(2 + h, l * 16 + 6);
      {
        const uint32_t* f = (const uint32_t*)(flags + r * 16 + ((r + 2 + 2 * (lane % 3)) & 7) * 2);
        const uint32_t evl = ev + 3 + (lane >= 3);
        uint32_t next = 0, cnt = 0;
        while (next < 6) {
          const uint32_t rdy = __ballot_sync(0xffffffff, (int32_t)(ld_relaxed(f) - evl) >= 0);
          while (next < (cnt == 0 ? 3 : 6) && ((rdy >> next) & 1)) {
            if (next == 3) mbar_wait(afree + 8, l);
            if (next == 5) mbar_wait(afree + 16, l);
            if (elect_one()) {
              const uint32_t bytes = next < 3 ? 12288 : 10240, reg = next < 3 ? 2 + next : next - 3;
              mbar_expect_tx(afull + (1 + next) * 8, bytes);
              bulk_g2s(abase + reg * 12288, hb + ((r + 2 + 2 * reg + (next < 3 ? 4 : 0)) & 7) * 1536 + (next < 3 ? 0 : 768), bytes, afull + (1 + next) * 8);
            }
            if (next == 0) STAMP(2 + h, l * 16 + 13);
            next++;
          }
          if (cnt == 0) {
            if (lane == 0) PUBWAIT<0>();
            __syncwarp();
            set_flags(flags + r * 2, ev + 4, lane);
          }
          if (++cnt > SPIN_LIMIT) __trap();
        }
        __syncwarp();
      }
      STAMP(2 + h, l * 16 + 7);
      mbar_wait(own, p0);
      STAMP(2 + h, l * 16 + 8);
      if (l == 0) {
        publish_chunk(g_act + (2 * 32 + half) * 4096 + r * 512, abase, flags + r * 2, ev + 6, lane);
        mbar_wait(afree, p0); p0 ^= 1;
        fetch_chunks<8, 1>(g_act + (2 * 32 + half) * 4096, flags, abase, afull, r, ev + 6, lane);
        STAMP(2 + h, l * 16 + 9);
        gather_stats(g_stats + (2 * 32 + half) * 512, sb + SM_STAT + h * 512, sb + B_STAT + h * 8, lane, tag);
      } else if (lane == 0) {
        tma_store(&tm_out, abase, 64 * r, 128 * cb + 64 * h); bulk_commit(); bulk_wait<0>();
      }
      STAMP(2 + h, l * 16 + 10);
    }
  } else {
    if (lane < 24) { g_kv[(0 * 8 + r) * 384 + cb * 24 + lane] = make_float4(0.f, 0.f, 0.f, 0.f); g_kv[(1 * 8 + r) * 384 + cb * 24 + lane] = make_float4(0.f, 0.f, 0.f, 0.f); }
    fence_gpu();
    const uint32_t tag = (epoch & 1) ^ 1;
    colsum_task(wqkv + 64 * r + 8 * (lane & 7), 3 * kD, true, 32 * cb, g_cs + ((r * 2 + 0) * 16 + cb) * 48 + 2 * (lane & 7), lane, tag);
    __nanosleep(500);
    colsum_gather(g_cs + (r * 2 + 0) * 16 * 48, sb + SM_CS, 48, lane, tag);
    fence_gpu();
    if (lane == 0) mbar_arrive(sb + B_CSRDY);
    STAMP(2, 48);
    if (lane == 1) prefetch_l2((const char*)wo + bid * 4096, 4096);
    if (lane == 2) prefetch_l2((const char*)w2 + bid * 11008, 11008);
    asm volatile("barrier.cluster.wait.aligned;" ::: "memory");
#pragma unroll 1
    for (int l = 0; l < 2; l++) {
      mbar_wait(sb + B_KVDONE, l);
      STAMP(2, 50 + l * 4);
      const float4* kv = g_kv + (l * 8 + r) * 384 + lane;
      float4 v[12];
      uint32_t cnt = 0;
      __nanosleep(KVDELAY);
      {
        const float4* pp = g_kv + (l * 8 + r) * 384 + (lane & 3) * 96 + 95;
        while (!__all_sync(0xffffffff, ld_relaxed_f4(pp).w == 16.f)) { if (++cnt > SPIN_LIMIT) __trap(); __nanosleep(KVSLEEP); }
      }
      STAMP(2, 51 + l * 4);
      while (true) {
        bool ok = true;
#pragma unroll
        for (int i = 0; i < 12; i++) v[i] = ld_relaxed_f4(kv + i * 32);
#pragma unroll
        for (int i = 0; i < 12; i++) ok = ok && v[i].w == 16.f;
        if (__all_sync(0xffffffff, ok)) break;
        if (++cnt > SPIN_LIMIT) __trap();
      }
      STAMP(2, 52 + l * 4);
#pragma unroll
      for (int hh = 0; hh < 4; hh++) {
        const float4 a = v[3 * hh], b = v[3 * hh + 1], c = v[3 * hh + 2];
        const float z0 = __shfl_sync(0xffffffff, c.z, lane & 3), z1 = __shfl_sync(0xffffffff, c.z, 4 + (lane & 3)),
                    z2 = __shfl_sync(0xffffffff, c.z, 8 + (lane & 3)), z3 = __shfl_sync(0xffffffff, c.z, 12 + (lane & 3));
        const uint32_t d = sb + SM_RING + 16384 + hh * 768 + lane * 8;
        sts_u2(d, pack_bf16(a.x, a.y), pack_bf16(a.z, b.x));
        sts_u2(d + 256, pack_bf16(b.y, b.z), pack_bf16(c.x, c.y));
        sts_u2(d + 512, pack_bf16(z0, z1), pack_bf16(z2, z3));
      }
      __syncwarp();
      if (lane == 0) mbar_arrive(sb + B_KVRDY);
      STAMP(2, 53 + l * 4);
      if (l == 0) {
        colsum_gather(g_cs + (r * 2 + 1) * 16 * 48, sb + SM_CS + 768, 44, lane, tag);
        if (lane == 0) mbar_arrive(sb + B_CSRDY + 8);
      }
    }
    if (lane == 0) g_epoch[bid * 8] = epoch + 1;
  }
  } else {
    asm volatile("setmaxnreg.inc.sync.aligned.u32 200;");
    const int lane = __shfl_sync(0xffffffff, threadIdx.x & 31, threadIdx.x & 31);
    const uint32_t epoch = ld_relaxed(g_epoch + bid * 8);
    const int wg0 = warp >> 2, lane0 = lane, half = cb * 2 + wg0, wg = wg0;
    const uint32_t sb0 = sb;
    STAMP(wg, 62);
    const uint32_t tag = (epoch + 1) & 1;
    uint32_t xr[16];
    uint32_t sph = 0;
    mbar_wait(sb0 + B_AFULL + wg0 * 64, 0);
#pragma unroll
    for (int s = 0; s < 4; s++)
      ldsm4(sb0 + wg0 * 65536 + (16 * (warp & 3) + 8 * ((lane0 >> 3) & 1) + (lane0 & 7)) * 128 + (((2 * s + (lane0 >> 4)) ^ (lane0 & 7)) << 4),
            xr[4 * s], xr[4 * s + 1], xr[4 * s + 2], xr[4 * s + 3]);
    asm volatile("barrier.cluster.wait.aligned;" ::: "memory");
    STAMP(wg, 63);

#pragma unroll 1
    for (int l = 0; l < 2; l++) {
      const uint32_t sb = opaque(sb0);
      const int lane = opaque(lane0), wg = opaque(wg0), wq = opaque(warp) & 3, g = lane >> 2, t = lane & 3;
      const uint32_t abase = sb + wg * 65536, afull = sb + B_AFULL + wg * 64, afree = sb + B_AFREE + wg * 24, own = sb + B_OWN + wg * 24;
      const uint32_t ring = sb + SM_RING;
      const uint32_t dA = desc_lo(abase, 16), dH = desc_lo(abase, 1024), dB = desc_lo(ring, 8192), dB2 = desc_lo(ring, 12288);
      constexpr int S4 = SLOT >> 4;
      uint32_t swa[4];
#pragma unroll
      for (int s = 0; s < 4; s++) swa[s] = abase + (16 * wq + 8 * ((lane >> 3) & 1) + (lane & 7)) * 128 + (((2 * s + (lane >> 4)) ^ (lane & 7)) << 4);
      auto wait_b = [&](int st) { mbar_wait(sb + B_BFULL + (st & 3) * 8, (st >> 2) & 1); };
      auto release_b = [&](int st) { if (lane == 0) mbar_arrive(sb + B_BEMPTY + (st & 3) * 8); };
      auto signal = [&](uint32_t bar) { __syncwarp(); if (lane == 0) mbar_arrive(bar); };
      const uint32_t chk = abase + (16 * wq + g) * 128 + (((2 * t) ^ g) << 4);
      auto bad_chunk = [&](int i, uint32_t tg) -> uint32_t { return (lds_u32(chk + i * 8192) ^ tg) | (lds_u32(chk + (i * 8192 + 1024)) ^ tg); };
      auto apar = [&](int i, int ph) -> uint32_t { return ((l & (i < 4 ? 4 : i < 7 ? 3 : 2)) ^ (i < 4 || ph == 0 ? ph : ph - 1)) & 1; };
      auto fetch_ok = [&](int i, int n, int ph, int str, int buf, uint32_t tg) {
        uint32_t bad = 0;
#pragma unroll
        for (int u = i; u < i + n; u++) mbar_wait(afull + u * 8, apar(u, ph));
#pragma unroll
        for (int u = i; u < i + n; u++) bad |= bad_chunk(u, tg);
        if (__builtin_expect(!__all_sync(0xffffffff, (bad & 1u) == 0), 0)) {
#pragma unroll 1
          for (int u = i; u < i + n; u++) {
            const uint4* src = g_act + (buf * 32 + opaque(half)) * 4096 + ((opaque(r) + str * u) & 7) * 512 + wq * 128 + opaque(lane);
            const uint32_t dst = abase + u * 8192 + wq * 2048 + opaque(lane) * 16;
            uint32_t cnt = 0;
            while (!__all_sync(0xffffffff, (bad_chunk(u, tg) & 1u) == 0)) {
#pragma unroll 1
              for (int v = 0; v < 4; v++) sts_u4(dst + v * 512, ld_relaxed_u4(src + v * 32));
              fence_async_smem();
              __syncwarp();
              HEALCNT();
              if (++cnt > SPIN_LIMIT) __trap();
            }
          }
        }
      };
      const uint32_t hchk = abase + (lane >> 4) * 2048 + ((lane >> 3) & 1) * 1024 + (2 * wq + ((lane >> 2) & 1)) * 128 + (lane & 3) * 32 + g * 4;
      const uint32_t hchk5 = hchk + (lane >= 16 ? 0 : 8192);
      auto bad_block = [&](int b, uint32_t tg) -> uint32_t {
        const uint32_t o = (b < 3 ? 2 + b : b - 3) * 12288;
        return (lds_u32(hchk + o) ^ tg) | (lds_u32(hchk + (o + 4096)) ^ tg) | (lds_u32(b < 3 ? hchk + (o + 8192) : hchk5 + o) ^ tg);
      };
      auto fetch_h_ok = [&](int b, int n, uint32_t tg) {
        uint32_t bad = 0;
#pragma unroll
        for (int u = b; u < b + n; u++) mbar_wait(afull + (1 + u) * 8, apar(1 + u, 3));
#pragma unroll
        for (int u = b; u < b + n; u++) bad |= bad_block(u, tg);
        if (__builtin_expect(!__all_sync(0xffffffff, (bad >> 31) == 0), 0)) {
#pragma unroll 1
          for (int u = b; u < b + n; u++) {
            const int ln = opaque(lane);
            const uint32_t off = (ln >> 4) * 1024 + wq * 256 + (ln & 15) * 16;
            const uint4* src = g_h + (opaque(half) * 8 + ((opaque(r) + 2 + 2 * (u % 3)) & 7)) * 1536 + (u < 3 ? 0 : 768) + off / 16;
            uint32_t cnt = 0;
            while (!__all_sync(0xffffffff, (bad_block(u, tg) >> 31) == 0)) {
#pragma unroll 1
              for (int v = 0; v < (u < 3 ? 6 : 5); v++) sts_u4(abase + (u < 3 ? 2 + u : u - 3) * 12288 + v * 2048 + off, ld_relaxed_u4(src + v * 128));
              fence_async_smem();
              __syncwarp();
              HEALCNT();
              if (++cnt > SPIN_LIMIT) __trap();
            }
          }
        }
      };
      auto peer_ready = [&]() {
        if (lane == 0) { mbar_arrive_remote(mapa(sb + B_PFREE + wg * 8, (r & 1) ^ 1)); if (wq == 0) mbar_expect_tx(sb + B_PRDY + wg * 8, 8192); }
      };
      auto send_partial = [&](const float (&v)[32], uint32_t land, uint32_t par) {
        mbar_wait(sb + B_PFREE + wg * 8, par);
        const uint32_t rdst = mapa(abase + land + (wq * 32 + lane) * 16, (r & 1) ^ 1), rbar = mapa(sb + B_PRDY + wg * 8, (r & 1) ^ 1);
#pragma unroll
        for (int i = 0; i < 4; i++)
          st_async_v4(rdst + i * 2048, pack_bf16(v[8 * i], v[8 * i + 1]), pack_bf16(v[8 * i + 2], v[8 * i + 3]),
                      pack_bf16(v[8 * i + 4], v[8 * i + 5]), pack_bf16(v[8 * i + 6], v[8 * i + 7]), rbar);
      };
      auto add_residual = [&](const float (&v)[32], uint32_t land, uint32_t par, float a0, float a1) {
        mbar_wait(sb + B_PRDY + wg * 8, par);
        uint4 p[4];
#pragma unroll
        for (int i = 0; i < 4; i++) p[i] = lds_u4(abase + land + i * 2048 + (wq * 32 + lane) * 16);
#pragma unroll
        for (int i = 0; i < 4; i++) {
          xr[4 * i] = pack_bf16(fmaf(a0, v[8 * i] + bf_lo(p[i].x), bf_lo(xr[4 * i])), fmaf(a0, v[8 * i + 1] + bf_hi(p[i].x), bf_hi(xr[4 * i])));
          xr[4 * i + 1] = pack_bf16(fmaf(a1, v[8 * i + 2] + bf_lo(p[i].y), bf_lo(xr[4 * i + 1])), fmaf(a1, v[8 * i + 3] + bf_hi(p[i].y), bf_hi(xr[4 * i + 1])));
          xr[4 * i + 2] = pack_bf16(fmaf(a0, v[8 * i + 4] + bf_lo(p[i].z), bf_lo(xr[4 * i + 2])), fmaf(a0, v[8 * i + 5] + bf_hi(p[i].z), bf_hi(xr[4 * i + 2])));
          xr[4 * i + 3] = pack_bf16(fmaf(a1, v[8 * i + 6] + bf_lo(p[i].w), bf_lo(xr[4 * i + 3])), fmaf(a1, v[8 * i + 7] + bf_hi(p[i].w), bf_hi(xr[4 * i + 3])));
        }
      };
      const uint32_t tmask = t == 0 ? 1u : 0u;
      auto store_chunk = [&](const uint32_t (&v)[16], uint32_t tg  , uint32_t msk) {
#pragma unroll
        for (int s = 0; s < 4; s++) stsm4(swa[s], (v[4 * s] & ~msk) | tg, (v[4 * s + 1] & ~msk) | tg, v[4 * s + 2], v[4 * s + 3]);
        fence_async_smem();
        signal(own);
      };
      auto stat_dst = [&](int ln) -> float2* { return g_stats + (ln * 32 + opaque(half)) * 512 + opaque(r) * 64 + 16 * wq + g; };
      const uint32_t stat_sm = sb + SM_STAT + (wg * 64 + 16 * wq + g) * 8;
      const uint32_t cs_sm = sb + SM_CS + 8 * t;
      const uint32_t ltag = l ^ 1;
      float rs0, rs1;
      {
        float ak[32], av[32], aq[32];
        STAMP(wg, l * 24 + 0);
        {
          wait_b(0);
          wg_fence();
          wgmma_n128_init<0, 0, HI_SW>(ak, av, dA, dB);
          static_for<1, 4>([&](auto K) { wgmma_n128<2 * K.value, 128 * K.value, HI_SW>(ak, av, dA, dB); });
          wg_commit();
          publish_stats(xr, stat_dst(2 * l), t, tag);
        }
        static_for<1, 8>([&](auto I) {
          constexpr int i = I.value;
          if (l == 0) mbar_wait(afull + i * 8, 0); else fetch_ok(i, 1, 0, 1, 2, tag);
          if (i == 1) STAMP(wg, l * 2 + 19);
          wait_b(i);
          wg_fence_in();
          static_for<0, 4>([&](auto K) { wgmma_n128<i * 512 + 2 * K.value, (i & 3) * S4 + 128 * K.value, HI_SW>(ak, av, dA, dB); });
          wg_commit();
          wg_wait<1>(); release_b(i - 1);
        });
        STAMP(wg, l * 24 + 1);
        auto q_stage = [&](auto I) {
          constexpr int i = I.value;
          wait_b(8 + i);
          wg_fence();
          static_for<0, 8>([&](auto K) {
            constexpr int k = K.value;
            if constexpr (i == 0 && k == 0) wgmma_n64_init<0, 0, HI_SW>(aq, dA, dB);
            else wgmma_n64<i * 1024 + (k >> 2) * 512 + 2 * (k & 3), i * S4 + 128 * k, HI_SW>(aq, dA, dB);
          });
          wg_commit();
        };
        if (l == 0) mbar_wait(sb + B_CSRDY, 0);
        mbar_wait(sb + B_STAT + wg * 8, sph); sph ^= 1;
        const float2 s0 = lds_f2(stat_sm), s1 = lds_f2(stat_sm + 64);
        const float y0 = s0.x * 1.4426950408889634f, y1 = s1.x * 1.4426950408889634f;
        const uint32_t pk_s = ring + (2 * wg) * SLOT + 16384;
        {
          float2 c[16];
#pragma unroll
          for (int j = 0; j < 16; j++) c[j] = lds_f2(cs_sm + (64 + 8 * j) * 4);
          wg_wait<0>(); release_b(7);
          fence_regs(ak); fence_regs(av);
          STAMP(wg, l * 24 + 2);
          uint32_t pk[16], pv[16];
#pragma unroll
          for (int j = 0; j < 8; j++) {
            pk[2 * j] = pack_bf16(phi_y(y0 * fmaf(s0.y, c[j].x, ak[4 * j])), phi_y(y0 * fmaf(s0.y, c[j].y, ak[4 * j + 1])));
            pk[2 * j + 1] = pack_bf16(phi_y(y1 * fmaf(s1.y, c[j].x, ak[4 * j + 2])), phi_y(y1 * fmaf(s1.y, c[j].y, ak[4 * j + 3])));
            pv[2 * j] = pack_bf16(s0.x * fmaf(s0.y, c[8 + j].x, av[4 * j]), s0.x * fmaf(s0.y, c[8 + j].y, av[4 * j + 1]));
            pv[2 * j + 1] = pack_bf16(s1.x * fmaf(s1.y, c[8 + j].x, av[4 * j + 2]), s1.x * fmaf(s1.y, c[8 + j].y, av[4 * j + 3]));
          }
#pragma unroll
          for (int s = 0; s < 4; s++) {
            stsm4(swa[s] + (pk_s - abase), pk[4 * s], pk[4 * s + 1], pk[4 * s + 2], pk[4 * s + 3]);
            stsm4(swa[s] + (pk_s - abase) + SLOT, pv[4 * s], pv[4 * s + 1], pv[4 * s + 2], pv[4 * s + 3]);
          }
        }
        STAMP(wg, 20 + l * 2);
        if (wg == 0) { asm volatile("bar.arrive 4, 256;" ::: "memory"); asm volatile("bar.sync 5, 256;" ::: "memory"); }
        else {
          asm volatile("bar.sync 4, 256;" ::: "memory");
          float c0[4] = {0.f, 0.f, 0.f, 0.f}, c1[4] = {0.f, 0.f, 0.f, 0.f}, z0[4] = {0.f, 0.f, 0.f, 0.f}, z1[4] = {0.f, 0.f, 0.f, 0.f};
          const int m = lane >> 3;
          const uint32_t va = ring + SLOT + 16384 + (8 * (m >> 1) + (lane & 7)) * 128 + (((2 * wq + (m & 1)) ^ (lane & 7)) << 4);
          const uint32_t pa = ring + 16384 + (8 * (m & 1) + (lane & 7)) * 128 + (((2 * wq + (m >> 1)) ^ (lane & 7)) << 4);
#pragma unroll
          for (int ks = 0; ks < 8; ks++) {
            uint32_t a0, a1, a2, a3, b0, b1, b2, b3;
            ldsm4t(va + (ks >> 2) * 2 * SLOT + (ks & 3) * 2048, a0, a1, a2, a3);
            ldsm4t(pa + (ks >> 2) * 2 * SLOT + (ks & 3) * 2048, b0, b1, b2, b3);
            mma16816(c0, a0, a1, a2, a3, b0, b1);
            mma16816(c1, a0, a1, a2, a3, b2, b3);
            mma16816(z0, 0x3f803f80u, 0x3f803f80u, 0x3f803f80u, 0x3f803f80u, b0, b1);
            mma16816(z1, 0x3f803f80u, 0x3f803f80u, 0x3f803f80u, 0x3f803f80u, b2, b3);
          }
          asm volatile("bar.arrive 5, 256;" ::: "memory");
          float* kv = (float*)(g_kv + (l * 8 + opaque(r)) * 384 + wq * 96 + lane);
          red_add_f4(kv, c0[0], c0[1], c1[0], 1.f);
          red_add_f4(kv + 128, c1[1], c0[2], c0[3], 1.f);
          red_add_f4(kv + 256, c1[2], c1[3], g == 0 ? z0[0] : g == 1 ? z0[1] : g == 2 ? z1[0] : z1[1], 1.f);
          signal(sb + B_KVDONE);
        }
        STAMP(wg, l * 24 + 3);
        q_stage(IC<0>{}); q_stage(IC<1>{}); q_stage(IC<2>{}); q_stage(IC<3>{});
        float2 c[8];
#pragma unroll
        for (int j = 0; j < 8; j++) c[j] = lds_f2(cs_sm + 8 * j * 4);
        wg_wait<3>(); release_b(8);
        wg_wait<2>(); release_b(9);
        wg_wait<1>(); release_b(10);
        wg_wait<0>(); release_b(11);
        fence_regs(aq);
        if (lane == 0) mbar_arrive(afree);
        peer_ready();
        STAMP(wg, l * 24 + 4);
        uint32_t pq[16];
#pragma unroll
        for (int j = 0; j < 8; j++) {
          pq[2 * j] = pack_bf16(phi_y(y0 * fmaf(s0.y, c[j].x, aq[4 * j])), phi_y(y0 * fmaf(s0.y, c[j].y, aq[4 * j + 1])));
          pq[2 * j + 1] = pack_bf16(phi_y(y1 * fmaf(s1.y, c[j].x, aq[4 * j + 2])), phi_y(y1 * fmaf(s1.y, c[j].y, aq[4 * j + 3])));
        }
        STAMP(wg, l * 24 + 5);
        mbar_wait(sb + B_KVRDY, l);
        STAMP(wg, l * 24 + 6);
        uint2 f[12];
#pragma unroll
        for (int i = 0; i < 12; i++) f[i] = lds_u2(ring + 16384 + i * 256 + lane * 8);
        float cn[4][8], cz[4][4];
#pragma unroll
        for (int hh = 0; hh < 4; hh++) {
          float c0[4] = {0.f, 0.f, 0.f, 0.f}, c1[4] = {0.f, 0.f, 0.f, 0.f};
          cz[hh][0] = cz[hh][1] = cz[hh][2] = cz[hh][3] = 0.f;
          mma16816(cz[hh], pq[4 * hh], pq[4 * hh + 1], pq[4 * hh + 2], pq[4 * hh + 3], f[3 * hh + 2].x, f[3 * hh + 2].y);
          mma16816(c0, pq[4 * hh], pq[4 * hh + 1], pq[4 * hh + 2], pq[4 * hh + 3], f[3 * hh].x, f[3 * hh].y);
          mma16816(c1, pq[4 * hh], pq[4 * hh + 1], pq[4 * hh + 2], pq[4 * hh + 3], f[3 * hh + 1].x, f[3 * hh + 1].y);
#pragma unroll
          for (int u = 0; u < 4; u++) { cn[hh][u] = c0[u]; cn[hh][4 + u] = c1[u]; }
        }
        uint32_t o[16];
#pragma unroll
        for (int hh = 0; hh < 4; hh++) {
          const float i0 = rcp(cz[hh][0] + 1e-6f), i1 = rcp(cz[hh][2] + 1e-6f);
          o[4 * hh] = pack_bf16(cn[hh][0] * i0, cn[hh][1] * i0); o[4 * hh + 1] = pack_bf16(cn[hh][2] * i1, cn[hh][3] * i1);
          o[4 * hh + 2] = pack_bf16(cn[hh][4] * i0, cn[hh][5] * i0); o[4 * hh + 3] = pack_bf16(cn[hh][6] * i1, cn[hh][7] * i1);
        }
        store_chunk(o, ltag & tmask, tmask);
        wg_bar(wg);
        STAMP(wg, l * 24 + 7);
      }
      {
        float ap[32], ao[32];
        wait_b(12);
        wg_fence();
        wgmma_n64_init<0, 0, HI_SW>(ap, dA, dB);
        static_for<1, 4>([&](auto K) { wgmma_n64<2 * K.value, 128 * K.value, HI_SW>(ap, dA, dB); });
        wgmma_n64_init<0, 512, HI_SW>(ao, dA, dB);
        static_for<1, 4>([&](auto K) { wgmma_n64<2 * K.value, 512 + 128 * K.value, HI_SW>(ao, dA, dB); });
        wg_commit();
        wait_b(13); wait_b(14); wait_b(15);
        wg_wait<0>(); release_b(12);
        static_for<1, 4>([&](auto I) {
          constexpr int i = I.value;
          if (i < 3) fetch_ok(i, i, 1, 2, 0, ltag);
          if (i == 1) STAMP(wg, l * 24 + 8);
          if (l == 1) STAMP(wg, 43 + i);
          wg_fence();
          static_for<0, 4>([&](auto K) { wgmma_n64<i * 512 + 2 * K.value, i * S4 + 128 * K.value, HI_SW>(ap, dA, dB); });
        });
        wg_commit();
        static_for<0, 12>([&](auto K) { wgmma_n64<(1 + K.value / 4) * 512 + 2 * (K.value & 3), (1 + K.value / 4) * S4 + 512 + 128 * (K.value & 3), HI_SW>(ao, dA, dB); });
        wg_commit();
        wg_wait<1>();
        fence_regs(ap);
        send_partial(ap, 4 * 8192, 0);
        wg_wait<0>(); release_b(13); release_b(14); release_b(15);
        fence_regs(ao);
        STAMP(wg, l * 24 + 9);
        add_residual(ao, 4 * 8192, 0, 1.f, 1.f);
        signal(afree);
        store_chunk(xr, ltag & tmask, tmask);
        wg_bar(wg);
        STAMP(wg, l * 24 + 10);
      }
      {
        float acc[88];
        {
          wait_b(16);
          wg_fence();
          wgmma_n176_init<0, 0, HI_SW>(acc, dA, dB);
          static_for<1, 4>([&](auto K) { wgmma_n176<2 * K.value, 128 * K.value, HI_SW>(acc, dA, dB); });
          wg_commit();
          publish_stats(xr, stat_dst(2 * l + 1), t, tag);
        }
        static_for<1, 8>([&](auto I) {
          constexpr int i = I.value;
          fetch_ok(i, 1, 2, 1, 1, ltag);
          if (i == 1) STAMP(wg, l * 24 + 11);
          wait_b(16 + i);
          wg_fence_in();
          static_for<0, 4>([&](auto K) { wgmma_n176<i * 512 + 2 * K.value, (i & 3) * S4 + 128 * K.value, HI_SW>(acc, dA, dB); });
          wg_commit();
          wg_wait<1>(); release_b(15 + i);
        });
        if (l == 0) mbar_wait(sb + B_CSRDY + 8, 0);
        mbar_wait(sb + B_STAT + wg * 8, sph); sph ^= 1;
        const float2 s0 = lds_f2(stat_sm), s1 = lds_f2(stat_sm + 64);
        float2 c[22];
#pragma unroll
        for (int j = 0; j < 22; j++) c[j] = lds_f2(cs_sm + (192 + 8 * j) * 4);
        const uint32_t sgn = ltag ? 0x80008000u : 0u;
        rs0 = ltag ? -s0.x : s0.x; rs1 = ltag ? -s1.x : s1.x;
        wg_wait<0>(); release_b(23);
        fence_regs(acc);
        if (lane == 0) mbar_arrive(afree);
        STAMP(wg, l * 24 + 12);
        const uint32_t hrow = abase + (lane >> 4) * 1024 + (2 * wq + ((lane >> 3) & 1)) * 128 + (lane & 7) * 16;
        wg_bar(wg);
#pragma unroll
        for (int b = 0; b < 2; b++) {
          uint32_t p[24];
#pragma unroll
          for (int u = 0; u < (b ? 10 : 12); u++) {
            const int j = 12 * b + u;
            p[2 * u] = pack_bf16_relu(fmaf(s0.y, c[j].x, acc[4 * j]), fmaf(s0.y, c[j].y, acc[4 * j + 1])) ^ sgn;
            p[2 * u + 1] = pack_bf16_relu(fmaf(s1.y, c[j].x, acc[4 * j + 2]), fmaf(s1.y, c[j].y, acc[4 * j + 3])) ^ sgn;
          }
#pragma unroll
          for (int s = 0; s < (b ? 5 : 6); s++) stsm4(hrow + (6 * b + s) * 2048, p[4 * s], p[4 * s + 1], p[4 * s + 2], p[4 * s + 3]);
          fence_async_smem(); signal(own + b * 8);
        }
        wg_bar(wg);
        STAMP(wg, l * 24 + 13);
      }
      {
        float ap[32], ao[32];
        float bp[32], bo[32];
        const uint32_t htag = ltag << 31;
        wait_b(24);
        wg_fence();
        wgmma_n128_init<0, 0, HI_NS>(ap, ao, dH, dB2);
        static_for<1, 6>([&](auto K) { wgmma_n128<128 * K.value, 128 * K.value, HI_NS>(ap, ao, dH, dB2); });
        wg_commit();
        wait_b(25);
        static_for<0, 5>([&](auto K) { wgmma_n128<768 + 128 * K.value, S4 + 128 * K.value, HI_NS>(ap, ao, dH, dB2); });
        wg_commit();
        wg_wait<1>(); release_b(24);
        wg_wait<0>(); release_b(25);
        if (lane == 0) mbar_arrive(afree + 8);
        static_for<0, 3>([&](auto I) {
          constexpr int i = I.value;
          fetch_h_ok(i, 1, htag);
          if (i == 0) STAMP(wg, l * 24 + 14);
          if (l == 1) STAMP(wg, 51 + i);
          wait_b(26 + i);
          wg_fence();
          static_for<0, 6>([&](auto K) { wgmma_n128<(2 + i) * 768 + 128 * K.value, ((26 + i) & 3) * S4 + 128 * K.value, HI_NS>(ap, ao, dH, dB2); });
          wg_commit();
          if (i > 0) { wg_wait<1>(); release_b(25 + i); }
          if (i == 1 && lane == 0) mbar_arrive(afree + 16);
          if (i == 2) peer_ready();
        });
        static_for<0, 3>([&](auto I) {
          constexpr int i = I.value;
          fetch_h_ok(3 + i, 1, htag);
          if (l == 1) STAMP(wg, 54 + i);
          wait_b(29 + i);
          wg_fence();
          static_for<0, 5>([&](auto K) {
            if constexpr (i == 0 && K.value == 0) wgmma_n64_init<0, S4, HI_NS>(bp, dH, dB2);
            else wgmma_n64<i * 768 + 128 * K.value, (1 + i) * S4 + 128 * K.value, HI_NS>(bp, dH, dB2);
          });
          wg_commit();
          if (i == 0) { wg_wait<1>(); release_b(28); }
        });
        wg_fence();
        static_for<0, 15>([&](auto K) {
          constexpr int i = K.value / 5, k = K.value % 5;
          if constexpr (K.value == 0) wgmma_n64_init<0, S4 + 768, HI_NS>(bo, dH, dB2);
          else wgmma_n64<i * 768 + 128 * k, (1 + i) * S4 + 768 + 128 * k, HI_NS>(bo, dH, dB2);
        });
        wg_commit();
        wg_wait<1>();
        fence_regs(ap); fence_regs(ao); fence_regs(bp);
        STAMP(wg, l * 24 + 15);
#pragma unroll
        for (int i = 0; i < 32; i++) ap[i] += bp[i];
        send_partial(ap, 3 * 12288, 1);
        wg_wait<0>(); release_b(29); release_b(30); release_b(31);
        fence_regs(bo);
#pragma unroll
        for (int i = 0; i < 32; i++) ao[i] += bo[i];
        wg_bar(wg);
        STAMP(wg, l * 24 + 16);
        add_residual(ao, 3 * 12288, 1, rs0, rs1);
        STAMP(wg, l * 24 + 17);
        {
          signal(afree);
          store_chunk(xr, l == 0 ? (tag & tmask) : 0u, l == 0 ? tmask : 0u);
          wg_bar(wg);
          STAMP(wg, l * 24 + 18);
        }
      }
      if (l == 0) asm volatile("" ::: "memory");
    }

  }
}

typedef CUresult (*EncodeFn)(CUtensorMap*, CUtensorMapDataType, cuuint32_t, void*, const cuuint64_t*, const cuuint64_t*, const cuuint32_t*,
                             const cuuint32_t*, CUtensorMapInterleave, CUtensorMapSwizzle, CUtensorMapL2promotion, CUtensorMapFloatOOBfill);

CUtensorMap make_map(EncodeFn enc, const void* ptr, uint64_t cols, uint64_t rows, uint32_t box_rows) {
  CUtensorMap m;
  cuuint64_t gd[2] = {cols, rows}, gs[1] = {cols * 2};
  cuuint32_t bd[2] = {64, box_rows}, es[2] = {1, 1};
  enc(&m, CU_TENSOR_MAP_DATA_TYPE_BFLOAT16, 2, const_cast<void*>(ptr), gd, gs, bd, es, CU_TENSOR_MAP_INTERLEAVE_NONE,
      CU_TENSOR_MAP_SWIZZLE_128B, CU_TENSOR_MAP_L2_PROMOTION_L2_128B, CU_TENSOR_MAP_FLOAT_OOB_FILL_NONE);
  return m;
}

}

extern "C" void kernel_launch(void* const* d_in, const int* in_sizes, int n_in, void* d_out, int out_size) {
  (void)in_sizes; (void)n_in; (void)out_size;
  const __nv_bfloat16* x = (const __nv_bfloat16*)d_in[0];
  const __nv_bfloat16* wqkv = (const __nv_bfloat16*)d_in[1];
  const __nv_bfloat16* wo = (const __nv_bfloat16*)d_in[2];
  const __nv_bfloat16* w1 = (const __nv_bfloat16*)d_in[4];
  const __nv_bfloat16* w2 = (const __nv_bfloat16*)d_in[5];
  void* fn = nullptr;
  cudaDriverEntryPointQueryResult q;
  cudaGetDriverEntryPoint("cuTensorMapEncodeTiled", &fn, cudaEnableDefault, &q);
  EncodeFn enc = (EncodeFn)fn;
  const CUtensorMap tm_x = make_map(enc, x, kD, kS, 64), tm_out = make_map(enc, d_out, kD, kS, 64),
                    tm_wqkv = make_map(enc, wqkv, 3 * kD, kD, 64), tm_wo = make_map(enc, wo, kD, kD, 64),
                    tm_w1 = make_map(enc, w1, kFF, kD, 64), tm_w2 = make_map(enc, w2, kD, kFF, 96), tm_w2s = make_map(enc, w2, kD, kFF, 80);
  cudaFuncSetAttribute(fused_kernel, cudaFuncAttributeMaxDynamicSharedMemorySize, SM_TOTAL);
  fused_kernel<<<128, 384, SM_TOTAL>>>(tm_x, tm_out, tm_wqkv, tm_wo, tm_w1, tm_w2, tm_w2s, wqkv, wo, w1, w2);
}
```

```cpp
#include <cuda_runtime.h>
#include <cuda_bf16.h>
#include <cuda.h>
#include <stdint.h>

#define NOCHECK 0
#define NOFENCE 0
#define KVSLEEP 40
#define KVDELAY 600
#define PUBWAIT bulk_wait_read
#define DELTA 0
#define DELTA0 0
#define QWAIT 1
#define PRIO 0
#define MAPPING 0
namespace {

constexpr int kS = 2048, kD = 512, kFF = 1376, kHS = 176;
constexpr uint32_t SM_RING = 131072, SLOT = 24576, SM_MISC = 229376;
constexpr uint32_t SM_STAT = SM_MISC;
constexpr uint32_t SM_CS = SM_MISC + 1024;
constexpr uint32_t SM_BAR = SM_CS + 1472;
constexpr uint32_t B_BFULL = SM_BAR, B_BEMPTY = SM_BAR + 32, B_AFULL = SM_BAR + 64  ,
                   B_AFREE = SM_BAR + 192  , B_OWN = SM_BAR + 240  , B_STAT = SM_BAR + 288  ,
                   B_CSRDY = SM_BAR + 304  , B_KVDONE = SM_BAR + 320, B_KVRDY = SM_BAR + 328,
                   B_PRDY = SM_BAR + 336  , B_PFREE = SM_BAR + 352  ;
constexpr uint32_t SM_TOTAL = SM_BAR + 368;
static_assert(SM_TOTAL <= 232448, "smem");
constexpr uint32_t SPIN_LIMIT = 1u << 22;

__device__ uint32_t g_epoch[128 * 8];
__device__ __align__(128) uint4 g_flags[32 * 8 * 8 * 2];
__device__ __align__(16) float4 g_cs[8 * 2 * 16 * 48];
__device__ __align__(128) float4 g_kv[2 * 8 * 384];
__device__ __align__(128) float2 g_stats[4 * 32 * 64 * 8];
__device__ __align__(1024) uint4 g_act[3 * 32 * 8 * 512];
__device__ __align__(1024) uint4 g_part[32 * 8 * 3 * 512];
#define HEALCNT() do {} while (0)
#define STAMP(role, i) do {} while (0)

__device__ __forceinline__ uint32_t smem_u32(const void* p) { return (uint32_t)__cvta_generic_to_shared(p); }
__device__ __forceinline__ void mbar_init(uint32_t bar, uint32_t cnt) { asm volatile("mbarrier.init.shared::cta.b64 [%0], %1;" :: "r"(bar), "r"(cnt)); }
__device__ __forceinline__ void mbar_expect_tx(uint32_t bar, uint32_t bytes) { asm volatile("mbarrier.arrive.expect_tx.shared::cta.b64 _, [%0], %1;" :: "r"(bar), "r"(bytes) : "memory"); }
__device__ __forceinline__ void mbar_arrive(uint32_t bar) { asm volatile("mbarrier.arrive.shared::cta.b64 _, [%0];" :: "r"(bar) : "memory"); }
__device__ __forceinline__ void mbar_arrive_remote(uint32_t bar) { asm volatile("mbarrier.arrive.shared::cluster.b64 _, [%0];" :: "r"(bar) : "memory"); }
__device__ __forceinline__ void mbar_wait(uint32_t bar, uint32_t parity) {
  asm volatile("{\n.reg .pred p;\n.reg .u32 c;\nmov.u32 c, 0;\nWAIT_LOOP:\n"
               "mbarrier.try_wait.parity.shared::cta.b64 p, [%0], %1;\n@p bra WAIT_DONE;\n"
               "add.u32 c, c, 1;\nsetp.lt.u32 p, c, %2;\n@p bra WAIT_LOOP;\ntrap;\nWAIT_DONE:\n}"
               :: "r"(bar), "r"(parity), "n"(SPIN_LIMIT) : "memory");
}
__device__ __forceinline__ uint32_t mapa(uint32_t addr, uint32_t rank) { uint32_t r; asm volatile("mapa.shared::cluster.u32 %0, %1, %2;" : "=r"(r) : "r"(addr), "r"(rank)); return r; }
__device__ __forceinline__ bool elect_one() { uint32_t p; asm volatile("{\n.reg .pred P;\nelect.sync _|P, 0xffffffff;\nselp.u32 %0, 1, 0, P;\n}" : "=r"(p)); return p; }
__device__ __forceinline__ void bulk_g2s(uint32_t dst, const void* src, uint32_t bytes, uint32_t bar) {
  asm volatile("cp.async.bulk.shared::cluster.global.mbarrier::complete_tx::bytes [%0], [%1], %2, [%3];" :: "r"(dst), "l"(src), "r"(bytes), "r"(bar) : "memory");
}
__device__ __forceinline__ void bulk_s2peer(uint32_t dst, uint32_t src, uint32_t bytes, uint32_t bar) {
  asm volatile("cp.async.bulk.shared::cluster.shared::cta.mbarrier::complete_tx::bytes [%0], [%1], %2, [%3];" :: "r"(dst), "r"(src), "r"(bytes), "r"(bar) : "memory");
}
__device__ __forceinline__ void bulk_s2g(void* dst, uint32_t src, uint32_t bytes) { asm volatile("cp.async.bulk.global.shared::cta.bulk_group [%0], [%1], %2;" :: "l"(dst), "r"(src), "r"(bytes) : "memory"); }
__device__ __forceinline__ void bulk_commit() { asm volatile("cp.async.bulk.commit_group;" ::: "memory"); }
template <int N> __device__ __forceinline__ void bulk_wait_read() { asm volatile("cp.async.bulk.wait_group.read %0;" :: "n"(N) : "memory"); }
template <int N> __device__ __forceinline__ void bulk_wait() { asm volatile("cp.async.bulk.wait_group %0;" :: "n"(N) : "memory"); }
__device__ __forceinline__ void tma_load(uint32_t dst, const CUtensorMap* m, int c0, int c1, uint32_t bar) {
  asm volatile("cp.async.bulk.tensor.2d.shared::cluster.global.mbarrier::complete_tx::bytes [%0], [%1, {%3, %4}], [%2];" :: "r"(dst), "l"(m), "r"(bar), "r"(c0), "r"(c1) : "memory");
}
__device__ __forceinline__ void tma_store(const CUtensorMap* m, uint32_t src, int c0, int c1) {
  asm volatile("cp.async.bulk.tensor.2d.global.shared::cta.bulk_group [%0, {%2, %3}], [%1];" :: "l"(m), "r"(src), "r"(c0), "r"(c1) : "memory");
}
__device__ __forceinline__ void prefetch_l2(const void* p, uint32_t bytes) { asm volatile("cp.async.bulk.prefetch.L2.global [%0], %1;" :: "l"(p), "r"(bytes) : "memory"); }
__device__ __forceinline__ void prefetch_map(const CUtensorMap* m) { asm volatile("prefetch.tensormap [%0];" :: "l"(m) : "memory"); }
__device__ __forceinline__ void fence_async_smem() { asm volatile("fence.proxy.async.shared::cta;" ::: "memory"); }
__device__ __forceinline__ void fence_async_global() { asm volatile("fence.proxy.async.global;" ::: "memory"); }
__device__ __forceinline__ void fence_gpu() { asm volatile("fence.acq_rel.gpu;" ::: "memory"); }
__device__ __forceinline__ void st_release(uint32_t* p, uint32_t v) { asm volatile("st.release.gpu.global.u32 [%0], %1;" :: "l"(p), "r"(v) : "memory"); }
__device__ __forceinline__ uint32_t ld_acquire(const uint32_t* p) { uint32_t v; asm volatile("ld.acquire.gpu.global.u32 %0, [%1];" : "=r"(v) : "l"(p) : "memory"); return v; }
__device__ __forceinline__ uint32_t ld_relaxed(const uint32_t* p) { uint32_t v; asm volatile("ld.relaxed.gpu.global.u32 %0, [%1];" : "=r"(v) : "l"(p) : "memory"); return v; }
__device__ __forceinline__ float2 ld_relaxed_f2(const void* p) { float2 v; asm volatile("ld.relaxed.gpu.global.v2.f32 {%0,%1}, [%2];" : "=f"(v.x), "=f"(v.y) : "l"(p) : "memory"); return v; }
__device__ __forceinline__ float4 ld_relaxed_f4(const void* p) { float4 v; asm volatile("ld.relaxed.gpu.global.v4.f32 {%0,%1,%2,%3}, [%4];" : "=f"(v.x), "=f"(v.y), "=f"(v.z), "=f"(v.w) : "l"(p) : "memory"); return v; }
__device__ __forceinline__ void st_relaxed_b64(void* p, float a, uint32_t b) {
  asm volatile("{\n.reg .b64 v;\nmov.b64 v, {%1, %2};\nst.relaxed.gpu.global.b64 [%0], v;\n}" :: "l"(p), "r"(__float_as_uint(a)), "r"(b) : "memory");
}
__device__ __forceinline__ void red_add_u32(uint32_t* p, uint32_t v) { asm volatile("red.relaxed.gpu.global.add.u32 [%0], %1;" :: "l"(p), "r"(v) : "memory"); }
__device__ __forceinline__ void red_add_f2(float* p, float a, float b) { asm volatile("red.relaxed.gpu.global.add.v2.f32 [%0], {%1, %2};" :: "l"(p), "f"(a), "f"(b) : "memory"); }
__device__ __forceinline__ void red_add_f4(float* p, float a, float b, float c, float d) { asm volatile("red.relaxed.gpu.global.add.v4.f32 [%0], {%1, %2, %3, %4};" :: "l"(p), "f"(a), "f"(b), "f"(c), "f"(d) : "memory"); }
__device__ __forceinline__ void st_async_v4(uint32_t dst, uint32_t a, uint32_t b, uint32_t c, uint32_t d, uint32_t bar) {
  asm volatile("st.async.weak.shared::cluster.mbarrier::complete_tx::bytes.v4.b32 [%0], {%1,%2,%3,%4}, [%5];" :: "r"(dst), "r"(a), "r"(b), "r"(c), "r"(d), "r"(bar) : "memory");
}
__device__ __forceinline__ void stsm4(uint32_t addr, uint32_t a, uint32_t b, uint32_t c, uint32_t d) {
  asm volatile("stmatrix.sync.aligned.m8n8.x4.shared.b16 [%0], {%1,%2,%3,%4};" :: "r"(addr), "r"(a), "r"(b), "r"(c), "r"(d) : "memory");
}
__device__ __forceinline__ void ldsm4(uint32_t addr, uint32_t& a, uint32_t& b, uint32_t& c, uint32_t& d) {
  asm volatile("ldmatrix.sync.aligned.m8n8.x4.shared.b16 {%0,%1,%2,%3}, [%4];" : "=r"(a), "=r"(b), "=r"(c), "=r"(d) : "r"(addr) : "memory");
}
__device__ __forceinline__ void ldsm4t(uint32_t addr, uint32_t& a, uint32_t& b, uint32_t& c, uint32_t& d) {
  asm volatile("ldmatrix.sync.aligned.m8n8.x4.trans.shared.b16 {%0,%1,%2,%3}, [%4];" : "=r"(a), "=r"(b), "=r"(c), "=r"(d) : "r"(addr) : "memory");
}
__device__ __forceinline__ float2 lds_f2(uint32_t addr) { float2 v; asm volatile("ld.shared.v2.f32 {%0,%1}, [%2];" : "=f"(v.x), "=f"(v.y) : "r"(addr) : "memory"); return v; }
__device__ __forceinline__ uint32_t lds_u32(uint32_t addr) { uint32_t v; asm volatile("ld.shared.u32 %0, [%1];" : "=r"(v) : "r"(addr) : "memory"); return v; }
__device__ __forceinline__ void sts_u4(uint32_t addr, uint4 v) { asm volatile("st.shared.v4.u32 [%0], {%1,%2,%3,%4};" :: "r"(addr), "r"(v.x), "r"(v.y), "r"(v.z), "r"(v.w) : "memory"); }
__device__ __forceinline__ uint4 ld_relaxed_u4(const void* p) { uint4 v; asm volatile("ld.relaxed.gpu.global.v4.u32 {%0,%1,%2,%3}, [%4];" : "=r"(v.x), "=r"(v.y), "=r"(v.z), "=r"(v.w) : "l"(p) : "memory"); return v; }
__device__ __forceinline__ void st_relaxed_u4(void* p, uint4 v) { asm volatile("st.relaxed.gpu.global.v4.u32 [%0], {%1,%2,%3,%4};" :: "l"(p), "r"(v.x), "r"(v.y), "r"(v.z), "r"(v.w) : "memory"); }
__device__ __forceinline__ void st_relaxed_u32(uint32_t* p, uint32_t v) { asm volatile("st.relaxed.gpu.global.u32 [%0], %1;" :: "l"(p), "r"(v) : "memory"); }
__device__ __forceinline__ void st_relaxed_f4(void* p, float a, float b, float c, uint32_t d) { asm volatile("st.relaxed.gpu.global.v4.b32 [%0], {%1,%2,%3,%4};" :: "l"(p), "r"(__float_as_uint(a)), "r"(__float_as_uint(b)), "r"(__float_as_uint(c)), "r"(d) : "memory"); }
__device__ __forceinline__ uint2 lds_u2(uint32_t addr) { uint2 v; asm volatile("ld.shared.v2.u32 {%0,%1}, [%2];" : "=r"(v.x), "=r"(v.y) : "r"(addr) : "memory"); return v; }
__device__ __forceinline__ uint4 lds_u4(uint32_t addr) { uint4 v; asm volatile("ld.shared.v4.u32 {%0,%1,%2,%3}, [%4];" : "=r"(v.x), "=r"(v.y), "=r"(v.z), "=r"(v.w) : "r"(addr) : "memory"); return v; }
__device__ __forceinline__ void sts_f2(uint32_t addr, float a, float b) { asm volatile("st.shared.v2.f32 [%0], {%1,%2};" :: "r"(addr), "f"(a), "f"(b) : "memory"); }
__device__ __forceinline__ void sts_u2(uint32_t addr, uint32_t a, uint32_t b) { asm volatile("st.shared.v2.u32 [%0], {%1,%2};" :: "r"(addr), "r"(a), "r"(b) : "memory"); }
__device__ __forceinline__ void sts_f4(uint32_t addr, float4 v) { asm volatile("st.shared.v4.f32 [%0], {%1,%2,%3,%4};" :: "r"(addr), "f"(v.x), "f"(v.y), "f"(v.z), "f"(v.w) : "memory"); }
__device__ __forceinline__ void mma16816(float (&c)[4], uint32_t a0, uint32_t a1, uint32_t a2, uint32_t a3, uint32_t b0, uint32_t b1) {
  asm volatile("mma.sync.aligned.m16n8k16.row.col.f32.bf16.bf16.f32 {%0,%1,%2,%3}, {%4,%5,%6,%7}, {%8,%9}, {%0,%1,%2,%3};"
               : "+f"(c[0]), "+f"(c[1]), "+f"(c[2]), "+f"(c[3]) : "r"(a0), "r"(a1), "r"(a2), "r"(a3), "r"(b0), "r"(b1));
}
__device__ __forceinline__ uint32_t pack_bf16(float lo, float hi) { uint32_t r; asm("cvt.rn.bf16x2.f32 %0, %1, %2;" : "=r"(r) : "f"(hi), "f"(lo)); return r; }
__device__ __forceinline__ uint32_t pack_bf16_relu(float lo, float hi) { uint32_t r; asm("cvt.rn.relu.bf16x2.f32 %0, %1, %2;" : "=r"(r) : "f"(hi), "f"(lo)); return r; }
__device__ __forceinline__ float bf_lo(uint32_t v) { return __uint_as_float(v << 16); }
__device__ __forceinline__ float bf_hi(uint32_t v) { return __uint_as_float(v & 0xffff0000u); }
__device__ __forceinline__ float ex2(float x) { float y; asm("ex2.approx.ftz.f32 %0, %1;" : "=f"(y) : "f"(x)); return y; }
__device__ __forceinline__ float rcp(float x) { float y; asm("rcp.approx.ftz.f32 %0, %1;" : "=f"(y) : "f"(x)); return y; }
__device__ __forceinline__ float phi_y(float y) { return fmaf(fmaxf(y, 1.4426950408889634e-6f), 0.6931471805599453f, ex2(fminf(y, 0.f))); }
__device__ __forceinline__ int opaque(int x) { int y; asm volatile("mov.u32 %0, %1;" : "=r"(y) : "r"(x)); return y; }
__device__ __forceinline__ void spin(int clks) { const uint32_t t0 = (uint32_t)clock(); while ((uint32_t)clock() - t0 < (uint32_t)clks) {} }
__device__ __forceinline__ void wg_fence() { asm volatile("wgmma.fence.sync.aligned;" ::: "memory"); }
__device__ __forceinline__ void wg_fence_in() { if (!NOFENCE) wg_fence(); }
__device__ __forceinline__ void wg_commit() { asm volatile("wgmma.commit_group.sync.aligned;" ::: "memory"); }
template <int N> __device__ __forceinline__ void wg_wait() { asm volatile("wgmma.wait_group.sync.aligned %0;" :: "n"(N) : "memory"); }
template <int N> __device__ __forceinline__ void fence_regs(float (&d)[N]) {
#pragma unroll
  for (int i = 0; i < N; i++) asm volatile("" : "+f"(d[i]) :: "memory");
}
template <int N> __device__ __forceinline__ void zero_regs(float (&d)[N]) {
#pragma unroll
  for (int i = 0; i < N; i++) d[i] = 0.f;
  fence_regs(d);
}
__device__ __forceinline__ void wg_bar(int wg) { if (wg == 0) asm volatile("bar.sync 1, 128;" ::: "memory"); else asm volatile("bar.sync 2, 128;" ::: "memory"); }
__device__ __forceinline__ uint32_t desc_lo(uint32_t addr, uint32_t lbo) { return ((addr & 0x3FFFF) >> 4) | ((lbo >> 4) << 16); }
constexpr uint32_t HI_SW = 0x40000040u;
constexpr uint32_t HI_NS = 0x00000008u;
template <int I> struct IC { static constexpr int value = I; };
template <int B, int E, class F> __device__ __forceinline__ void static_for(F&& f) {
  if constexpr (B < E) { f(IC<B>{}); static_for<B + 1, E>(f); }
}

template <int OA, int OB, uint32_t HA>
__device__ __forceinline__ void wgmma_n64_init(float (&d)[32], uint32_t la, uint32_t lb) {
  asm volatile("{\n.reg .pred p;\n.reg .b32 ta, tb;\n.reg .b64 da, db;\n"
    "setp.ne.b32 p, 0, 0;\nadd.u32 ta, %32, %34;\nadd.u32 tb, %33, %35;\n"
    "mov.b64 da, {ta, %36};\nmov.b64 db, {tb, 0x40000040};\n"
    "wgmma.mma_async.sync.aligned.m64n64k16.f32.bf16.bf16 "
    "{%0, %1, %2, %3, %4, %5, %6, %7, %8, %9, %10, %11, %12, %13, %14, %15, "
    "%16, %17, %18, %19, %20, %21, %22, %23, %24, %25, %26, %27, %28, %29, %30, %31}, "
    "da, db, p, 1, 1, 0, 1;\n}"
    : "=f"(d[0]), "=f"(d[1]), "=f"(d[2]), "=f"(d[3]), "=f"(d[4]), "=f"(d[5]), "=f"(d[6]), "=f"(d[7]),
      "=f"(d[8]), "=f"(d[9]), "=f"(d[10]), "=f"(d[11]), "=f"(d[12]), "=f"(d[13]), "=f"(d[14]), "=f"(d[15]),
      "=f"(d[16]), "=f"(d[17]), "=f"(d[18]), "=f"(d[19]), "=f"(d[20]), "=f"(d[21]), "=f"(d[22]), "=f"(d[23]),
      "=f"(d[24]), "=f"(d[25]), "=f"(d[26]), "=f"(d[27]), "=f"(d[28]), "=f"(d[29]), "=f"(d[30]), "=f"(d[31])
    : "r"(la), "r"(lb), "n"(OA), "n"(OB), "n"(HA));
}
template <int OA, int OB, uint32_t HA>
__device__ __forceinline__ void wgmma_n128_init(float (&d)[32], float (&e)[32], uint32_t la, uint32_t lb) {
  asm volatile("{\n.reg .pred p;\n.reg .b32 ta, tb;\n.reg .b64 da, db;\n"
    "setp.ne.b32 p, 0, 0;\nadd.u32 ta, %64, %66;\nadd.u32 tb, %65, %67;\n"
    "mov.b64 da, {ta, %68};\nmov.b64 db, {tb, 0x40000040};\n"
    "wgmma.mma_async.sync.aligned.m64n128k16.f32.bf16.bf16 "
    "{%0, %1, %2, %3, %4, %5, %6, %7, %8, %9, %10, %11, %12, %13, %14, %15, "
    "%16, %17, %18, %19, %20, %21, %22, %23, %24, %25, %26, %27, %28, %29, %30, %31, "
    "%32, %33, %34, %35, %36, %37, %38, %39, %40, %41, %42, %43, %44, %45, %46, %47, "
    "%48, %49, %50, %51, %52, %53, %54, %55, %56, %57, %58, %59, %60, %61, %62, %63}, "
    "da, db, p, 1, 1, 0, 1;\n}"
    : "=f"(d[0]), "=f"(d[1]), "=f"(d[2]), "=f"(d[3]), "=f"(d[4]), "=f"(d[5]), "=f"(d[6]), "=f"(d[7]),
      "=f"(d[8]), "=f"(d[9]), "=f"(d[10]), "=f"(d[11]), "=f"(d[12]), "=f"(d[13]), "=f"(d[14]), "=f"(d[15]),
      "=f"(d[16]), "=f"(d[17]), "=f"(d[18]), "=f"(d[19]), "=f"(d[20]), "=f"(d[21]), "=f"(d[22]), "=f"(d[23]),
      "=f"(d[24]), "=f"(d[25]), "=f"(d[26]), "=f"(d[27]), "=f"(d[28]), "=f"(d[29]), "=f"(d[30]), "=f"(d[31]),
      "=f"(e[0]), "=f"(e[1]), "=f"(e[2]), "=f"(e[3]), "=f"(e[4]), "=f"(e[5]), "=f"(e[6]), "=f"(e[7]),
      "=f"(e[8]), "=f"(e[9]), "=f"(e[10]), "=f"(e[11]), "=f"(e[12]), "=f"(e[13]), "=f"(e[14]), "=f"(e[15]),
      "=f"(e[16]), "=f"(e[17]), "=f"(e[18]), "=f"(e[19]), "=f"(e[20]), "=f"(e[21]), "=f"(e[22]), "=f"(e[23]),
      "=f"(e[24]), "=f"(e[25]), "=f"(e[26]), "=f"(e[27]), "=f"(e[28]), "=f"(e[29]), "=f"(e[30]), "=f"(e[31])
    : "r"(la), "r"(lb), "n"(OA), "n"(OB), "n"(HA));
}
template <int OA, int OB, uint32_t HA>
__device__ __forceinline__ void wgmma_n176_init(float (&d)[88], uint32_t la, uint32_t lb) {
  asm volatile("{\n.reg .pred p;\n.reg .b32 ta, tb;\n.reg .b64 da, db;\n"
    "setp.ne.b32 p, 0, 0;\nadd.u32 ta, %88, %90;\nadd.u32 tb, %89, %91;\n"
    "mov.b64 da, {ta, %92};\nmov.b64 db, {tb, 0x40000040};\n"
    "wgmma.mma_async.sync.aligned.m64n176k16.f32.bf16.bf16 "
    "{%0, %1, %2, %3, %4, %5, %6, %7, %8, %9, %10, %11, %12, %13, %14, %15, "
    "%16, %17, %18, %19, %20, %21, %22, %23, %24, %25, %26, %27, %28, %29, %30, %31, "
    "%32, %33, %34, %35, %36, %37, %38, %39, %40, %41, %42, %43, %44, %45, %46, %47, "
    "%48, %49, %50, %51, %52, %53, %54, %55, %56, %57, %58, %59, %60, %61, %62, %63, "
    "%64, %65, %66, %67, %68, %69, %70, %71, %72, %73, %74, %75, %76, %77, %78, %79, "
    "%80, %81, %82, %83, %84, %85, %86, %87}, "
    "da, db, p, 1, 1, 0, 1;\n}"
    : "=f"(d[0]), "=f"(d[1]), "=f"(d[2]), "=f"(d[3]), "=f"(d[4]), "=f"(d[5]), "=f"(d[6]), "=f"(d[7]),
      "=f"(d[8]), "=f"(d[9]), "=f"(d[10]), "=f"(d[11]), "=f"(d[12]), "=f"(d[13]), "=f"(d[14]), "=f"(d[15]),
      "=f"(d[16]), "=f"(d[17]), "=f"(d[18]), "=f"(d[19]), "=f"(d[20]), "=f"(d[21]), "=f"(d[22]), "=f"(d[23]),
      "=f"(d[24]), "=f"(d[25]), "=f"(d[26]), "=f"(d[27]), "=f"(d[28]), "=f"(d[29]), "=f"(d[30]), "=f"(d[31]),
      "=f"(d[32]), "=f"(d[33]), "=f"(d[34]), "=f"(d[35]), "=f"(d[36]), "=f"(d[37]), "=f"(d[38]), "=f"(d[39]),
      "=f"(d[40]), "=f"(d[41]), "=f"(d[42]), "=f"(d[43]), "=f"(d[44]), "=f"(d[45]), "=f"(d[46]), "=f"(d[47]),
      "=f"(d[48]), "=f"(d[49]), "=f"(d[50]), "=f"(d[51]), "=f"(d[52]), "=f"(d[53]), "=f"(d[54]), "=f"(d[55]),
      "=f"(d[56]), "=f"(d[57]), "=f"(d[58]), "=f"(d[59]), "=f"(d[60]), "=f"(d[61]), "=f"(d[62]), "=f"(d[63]),
      "=f"(d[64]), "=f"(d[65]), "=f"(d[66]), "=f"(d[67]), "=f"(d[68]), "=f"(d[69]), "=f"(d[70]), "=f"(d[71]),
      "=f"(d[72]), "=f"(d[73]), "=f"(d[74]), "=f"(d[75]), "=f"(d[76]), "=f"(d[77]), "=f"(d[78]), "=f"(d[79]),
      "=f"(d[80]), "=f"(d[81]), "=f"(d[82]), "=f"(d[83]), "=f"(d[84]), "=f"(d[85]), "=f"(d[86]), "=f"(d[87])
    : "r"(la), "r"(lb), "n"(OA), "n"(OB), "n"(HA));
}
template <int OA, int OB, uint32_t HA>
__device__ __forceinline__ void wgmma_n64(float (&d)[32], uint32_t la, uint32_t lb) {
  asm volatile("{\n.reg .pred p;\n.reg .b32 ta, tb;\n.reg .b64 da, db;\n"
    "setp.eq.b32 p, 0, 0;\nadd.u32 ta, %32, %34;\nadd.u32 tb, %33, %35;\n"
    "mov.b64 da, {ta, %36};\nmov.b64 db, {tb, 0x40000040};\n"
    "wgmma.mma_async.sync.aligned.m64n64k16.f32.bf16.bf16 "
    "{%0, %1, %2, %3, %4, %5, %6, %7, %8, %9, %10, %11, %12, %13, %14, %15, "
    "%16, %17, %18, %19, %20, %21, %22, %23, %24, %25, %26, %27, %28, %29, %30, %31}, "
    "da, db, p, 1, 1, 0, 1;\n}"
    : "+f"(d[0]), "+f"(d[1]), "+f"(d[2]), "+f"(d[3]), "+f"(d[4]), "+f"(d[5]), "+f"(d[6]), "+f"(d[7]),
      "+f"(d[8]), "+f"(d[9]), "+f"(d[10]), "+f"(d[11]), "+f"(d[12]), "+f"(d[13]), "+f"(d[14]), "+f"(d[15]),
      "+f"(d[16]), "+f"(d[17]), "+f"(d[18]), "+f"(d[19]), "+f"(d[20]), "+f"(d[21]), "+f"(d[22]), "+f"(d[23]),
      "+f"(d[24]), "+f"(d[25]), "+f"(d[26]), "+f"(d[27]), "+f"(d[28]), "+f"(d[29]), "+f"(d[30]), "+f"(d[31])
    : "r"(la), "r"(lb), "n"(OA), "n"(OB), "n"(HA));
}
template <int OA, int OB, uint32_t HA>
__device__ __forceinline__ void wgmma_n128(float (&d)[32], float (&e)[32], uint32_t la, uint32_t lb) {
  asm volatile("{\n.reg .pred p;\n.reg .b32 ta, tb;\n.reg .b64 da, db;\n"
    "setp.eq.b32 p, 0, 0;\nadd.u32 ta, %64, %66;\nadd.u32 tb, %65, %67;\n"
    "mov.b64 da, {ta, %68};\nmov.b64 db, {tb, 0x40000040};\n"
    "wgmma.mma_async.sync.aligned.m64n128k16.f32.bf16.bf16 "
    "{%0, %1, %2, %3, %4, %5, %6, %7, %8, %9, %10, %11, %12, %13, %14, %15, "
    "%16, %17, %18, %19, %20, %21, %22, %23, %24, %25, %26, %27, %28, %29, %30, %31, "
    "%32, %33, %34, %35, %36, %37, %38, %39, %40, %41, %42, %43, %44, %45, %46, %47, "
    "%48, %49, %50, %51, %52, %53, %54, %55, %56, %57, %58, %59, %60, %61, %62, %63}, "
    "da, db, p, 1, 1, 0, 1;\n}"
    : "+f"(d[0]), "+f"(d[1]), "+f"(d[2]), "+f"(d[3]), "+f"(d[4]), "+f"(d[5]), "+f"(d[6]), "+f"(d[7]),
      "+f"(d[8]), "+f"(d[9]), "+f"(d[10]), "+f"(d[11]), "+f"(d[12]), "+f"(d[13]), "+f"(d[14]), "+f"(d[15]),
      "+f"(d[16]), "+f"(d[17]), "+f"(d[18]), "+f"(d[19]), "+f"(d[20]), "+f"(d[21]), "+f"(d[22]), "+f"(d[23]),
      "+f"(d[24]), "+f"(d[25]), "+f"(d[26]), "+f"(d[27]), "+f"(d[28]), "+f"(d[29]), "+f"(d[30]), "+f"(d[31]),
      "+f"(e[0]), "+f"(e[1]), "+f"(e[2]), "+f"(e[3]), "+f"(e[4]), "+f"(e[5]), "+f"(e[6]), "+f"(e[7]),
      "+f"(e[8]), "+f"(e[9]), "+f"(e[10]), "+f"(e[11]), "+f"(e[12]), "+f"(e[13]), "+f"(e[14]), "+f"(e[15]),
      "+f"(e[16]), "+f"(e[17]), "+f"(e[18]), "+f"(e[19]), "+f"(e[20]), "+f"(e[21]), "+f"(e[22]), "+f"(e[23]),
      "+f"(e[24]), "+f"(e[25]), "+f"(e[26]), "+f"(e[27]), "+f"(e[28]), "+f"(e[29]), "+f"(e[30]), "+f"(e[31])
    : "r"(la), "r"(lb), "n"(OA), "n"(OB), "n"(HA));
}
template <int OA, int OB, uint32_t HA>
__device__ __forceinline__ void wgmma_n176(float (&d)[88], uint32_t la, uint32_t lb) {
  asm volatile("{\n.reg .pred p;\n.reg .b32 ta, tb;\n.reg .b64 da, db;\n"
    "setp.eq.b32 p, 0, 0;\nadd.u32 ta, %88, %90;\nadd.u32 tb, %89, %91;\n"
    "mov.b64 da, {ta, %92};\nmov.b64 db, {tb, 0x40000040};\n"
    "wgmma.mma_async.sync.aligned.m64n176k16.f32.bf16.bf16 "
    "{%0, %1, %2, %3, %4, %5, %6, %7, %8, %9, %10, %11, %12, %13, %14, %15, "
    "%16, %17, %18, %19, %20, %21, %22, %23, %24, %25, %26, %27, %28, %29, %30, %31, "
    "%32, %33, %34, %35, %36, %37, %38, %39, %40, %41, %42, %43, %44, %45, %46, %47, "
    "%48, %49, %50, %51, %52, %53, %54, %55, %56, %57, %58, %59, %60, %61, %62, %63, "
    "%64, %65, %66, %67, %68, %69, %70, %71, %72, %73, %74, %75, %76, %77, %78, %79, "
    "%80, %81, %82, %83, %84, %85, %86, %87}, "
    "da, db, p, 1, 1, 0, 1;\n}"
    : "+f"(d[0]), "+f"(d[1]), "+f"(d[2]), "+f"(d[3]), "+f"(d[4]), "+f"(d[5]), "+f"(d[6]), "+f"(d[7]),
      "+f"(d[8]), "+f"(d[9]), "+f"(d[10]), "+f"(d[11]), "+f"(d[12]), "+f"(d[13]), "+f"(d[14]), "+f"(d[15]),
      "+f"(d[16]), "+f"(d[17]), "+f"(d[18]), "+f"(d[19]), "+f"(d[20]), "+f"(d[21]), "+f"(d[22]), "+f"(d[23]),
      "+f"(d[24]), "+f"(d[25]), "+f"(d[26]), "+f"(d[27]), "+f"(d[28]), "+f"(d[29]), "+f"(d[30]), "+f"(d[31]),
      "+f"(d[32]), "+f"(d[33]), "+f"(d[34]), "+f"(d[35]), "+f"(d[36]), "+f"(d[37]), "+f"(d[38]), "+f"(d[39]),
      "+f"(d[40]), "+f"(d[41]), "+f"(d[42]), "+f"(d[43]), "+f"(d[44]), "+f"(d[45]), "+f"(d[46]), "+f"(d[47]),
      "+f"(d[48]), "+f"(d[49]), "+f"(d[50]), "+f"(d[51]), "+f"(d[52]), "+f"(d[53]), "+f"(d[54]), "+f"(d[55]),
      "+f"(d[56]), "+f"(d[57]), "+f"(d[58]), "+f"(d[59]), "+f"(d[60]), "+f"(d[61]), "+f"(d[62]), "+f"(d[63]),
      "+f"(d[64]), "+f"(d[65]), "+f"(d[66]), "+f"(d[67]), "+f"(d[68]), "+f"(d[69]), "+f"(d[70]), "+f"(d[71]),
      "+f"(d[72]), "+f"(d[73]), "+f"(d[74]), "+f"(d[75]), "+f"(d[76]), "+f"(d[77]), "+f"(d[78]), "+f"(d[79]),
      "+f"(d[80]), "+f"(d[81]), "+f"(d[82]), "+f"(d[83]), "+f"(d[84]), "+f"(d[85]), "+f"(d[86]), "+f"(d[87])
    : "r"(la), "r"(lb), "n"(OA), "n"(OB), "n"(HA));
}

__device__ __forceinline__ void publish_stats(const uint32_t (&xr)[16], float2* dst  , int t, uint32_t tag) {
  float s0 = 0.f, s1 = 0.f;
#pragma unroll
  for (int j = 0; j < 8; j++) { s0 += bf_lo(xr[2 * j]) + bf_hi(xr[2 * j]); s1 += bf_lo(xr[2 * j + 1]) + bf_hi(xr[2 * j + 1]); }
  s0 += __shfl_xor_sync(0xffffffff, s0, 1); s1 += __shfl_xor_sync(0xffffffff, s1, 1);
  s0 += __shfl_xor_sync(0xffffffff, s0, 2); s1 += __shfl_xor_sync(0xffffffff, s1, 2);
  const float m0 = s0 * (1.f / 64.f), m1 = s1 * (1.f / 64.f);
  float q0 = 0.f, q1 = 0.f;
#pragma unroll
  for (int j = 0; j < 8; j++) {
    float a = bf_lo(xr[2 * j]) - m0, b = bf_hi(xr[2 * j]) - m0, c = bf_lo(xr[2 * j + 1]) - m1, d = bf_hi(xr[2 * j + 1]) - m1;
    q0 = fmaf(a, a, q0); q0 = fmaf(b, b, q0); q1 = fmaf(c, c, q1); q1 = fmaf(d, d, q1);
  }
  q0 += __shfl_xor_sync(0xffffffff, q0, 1); q1 += __shfl_xor_sync(0xffffffff, q1, 1);
  q0 += __shfl_xor_sync(0xffffffff, q0, 2); q1 += __shfl_xor_sync(0xffffffff, q1, 2);
  if (t < 2) st_relaxed_b64(dst + 8 * t, t ? s1 : s0, (__float_as_uint(t ? q1 : q0) & ~1u) | tag);
}

__device__ __forceinline__ void gather_stats(const float2* src  , uint32_t sm_dst, uint32_t bar, int lane, uint32_t tag) {
  const float2* p = src + lane * 2;
  float4 v[8];
  uint32_t cnt = 0;
  while (true) {
#pragma unroll
    for (int i = 0; i < 8; i++) v[i] = ld_relaxed_f4(p + i * 64);
    uint32_t bad = 0;
#pragma unroll
    for (int i = 0; i < 8; i++) bad |= (__float_as_uint(v[i].y) ^ tag) | (__float_as_uint(v[i].w) ^ tag);
    if (__all_sync(0xffffffff, (bad & 1u) == 0)) break;
    if (++cnt > SPIN_LIMIT) __trap();
    __nanosleep(100);
  }
  float sa = 0.f, sb = 0.f, qa = 0.f, qb = 0.f;
#pragma unroll
  for (int i = 0; i < 8; i++) { sa += v[i].x; qa += v[i].y; sb += v[i].z; qb += v[i].w; }
  const float ma = sa * (1.f / 512.f), mb = sb * (1.f / 512.f);
  float da = 0.f, db = 0.f;
#pragma unroll
  for (int i = 0; i < 8; i++) {
    const float a = v[i].x * (1.f / 64.f) - ma, b = v[i].z * (1.f / 64.f) - mb;
    da = fmaf(a, a, da); db = fmaf(b, b, db);
  }
  sts_f4(sm_dst + lane * 16, make_float4(rsqrtf(fmaf(da, 64.f, qa) * (1.f / 512.f) + 1e-5f), -ma, rsqrtf(fmaf(db, 64.f, qb) * (1.f / 512.f) + 1e-5f), -mb));
  __syncwarp();
  if (lane == 0) mbar_arrive(bar);
}

__device__ __forceinline__ void colsum_task(const __nv_bfloat16* p  , int pitch, bool ok, int row0, float4* dst  , int lane, uint32_t tag) {
  const int rg = lane >> 3;
  float a[8];
#pragma unroll
  for (int i = 0; i < 8; i++) a[i] = 0.f;
  if (ok) {
    uint4 v[8];
#pragma unroll
    for (int i = 0; i < 8; i++) v[i] = __ldg((const uint4*)(p + (size_t)(row0 + 4 * i + rg) * pitch));
#pragma unroll
    for (int i = 0; i < 8; i++) {
      a[0] += bf_lo(v[i].x); a[1] += bf_hi(v[i].x); a[2] += bf_lo(v[i].y); a[3] += bf_hi(v[i].y);
      a[4] += bf_lo(v[i].z); a[5] += bf_hi(v[i].z); a[6] += bf_lo(v[i].w); a[7] += bf_hi(v[i].w);
    }
  }
#pragma unroll
  for (int i = 0; i < 8; i++) { a[i] += __shfl_xor_sync(0xffffffff, a[i], 8); a[i] += __shfl_xor_sync(0xffffffff, a[i], 16); }
  if (rg == 0) {
    st_relaxed_f4(dst, a[0], a[1], a[2], (__float_as_uint(a[3]) & ~1u) | tag);
    st_relaxed_f4(dst + 1, a[4], a[5], a[6], (__float_as_uint(a[7]) & ~1u) | tag);
  }
}
__device__ __forceinline__ void colsum_gather(const float4* src, uint32_t sm_dst, int nunits, int lane, uint32_t tag) {
#pragma unroll 1
  for (int j = 0; j < 3; j++) {
    const float4* p = src + (lane >> 4) * 8 * 48 + j * 16 + (lane & 15);
    float4 v[8];
    uint32_t cnt = 0;
    while (true) {
      uint32_t bad = 0;
#pragma unroll
      for (int i = 0; i < 8; i++) v[i] = ld_relaxed_f4(p + i * 48);
#pragma unroll
      for (int i = 0; i < 8; i++) bad |= __float_as_uint(v[i].w) ^ tag;
      if (__all_sync(0xffffffff, (bad & 1u) == 0)) break;
      if (++cnt > SPIN_LIMIT) __trap();
    }
    float4 a = v[0];
#pragma unroll
    for (int i = 1; i < 8; i++) { a.x += v[i].x; a.y += v[i].y; a.z += v[i].z; a.w += v[i].w; }
    a.x += __shfl_xor_sync(0xffffffff, a.x, 16); a.y += __shfl_xor_sync(0xffffffff, a.y, 16);
    a.z += __shfl_xor_sync(0xffffffff, a.z, 16); a.w += __shfl_xor_sync(0xffffffff, a.w, 16);
    if (lane < 16 && j * 16 + lane < nunits) sts_f4(sm_dst + (j * 16 + lane) * 16, a);
  }
  __syncwarp();
}

__device__ __forceinline__ void wait_flag_acq(const uint32_t* f, uint32_t ev) {
  uint32_t cnt = 0;
  while ((int32_t)(ld_acquire(f) - ev) < 0) { if (++cnt > SPIN_LIMIT) __trap(); }
}
__device__ __forceinline__ void wait_flags(const uint32_t* f  , uint32_t ev) {
  uint32_t cnt = 0;
  while (!__all_sync(0xffffffff, (int32_t)(ld_relaxed(f) - ev) >= 0)) { if (++cnt > SPIN_LIMIT) __trap(); }
}
__device__ __forceinline__ void set_flags(uint4* flag  , uint32_t ev, int lane) {
  if (lane < 16) asm volatile("st.relaxed.gpu.global.v4.u32 [%0], {%1,%1,%1,%1};" :: "l"(flag + (lane >> 1) * 16 + (lane & 1)), "r"(ev) : "memory");
}
__device__ __forceinline__ void publish_chunk(uint4* gdst, uint32_t src, uint4* flag, uint32_t ev, int lane) {
  if (lane == 0) { bulk_s2g(gdst, src, 8192); bulk_commit(); PUBWAIT<0>(); }
  __syncwarp();
  set_flags(flag, ev, lane);
}
template <int N, int STR>
__device__ __forceinline__ void fetch_chunks(const uint4* gbuf  , const uint4* flags, uint32_t abase, uint32_t afull, int r, uint32_t ev, int lane) {
  const uint32_t* f = (const uint32_t*)(flags + r * 16 + ((r + STR * lane) & 7) * 2);
  uint32_t todo = (1u << N) - 2, cnt = 0;
  while (todo) {
    const uint32_t rdy = __ballot_sync(0xffffffff, (int32_t)(ld_relaxed(f) - ev) >= 0) & todo;
#pragma unroll
    for (int i = 1; i < N; i++) {
      if ((rdy >> i) & 1) {
        if (elect_one()) {
          mbar_expect_tx(afull + i * 8, 8192);
          bulk_g2s(abase + i * 8192, gbuf + ((r + STR * i) & 7) * 512, 8192, afull + i * 8);
        }
      }
    }
    todo &= ~rdy;
    if (++cnt > SPIN_LIMIT) __trap();
  }
  __syncwarp();
}

__global__ void __cluster_dims__(2, 1, 1) __launch_bounds__(384, 1)
fused_kernel(const __grid_constant__ CUtensorMap tm_x, const __grid_constant__ CUtensorMap tm_out,
             const __grid_constant__ CUtensorMap tm_wqkv, const __grid_constant__ CUtensorMap tm_wo,
             const __grid_constant__ CUtensorMap tm_w1, const __grid_constant__ CUtensorMap tm_w2,
             const __nv_bfloat16* __restrict__ wqkv, const __nv_bfloat16* __restrict__ wo,
             const __nv_bfloat16* __restrict__ w1, const __nv_bfloat16* __restrict__ w2) {
  extern __shared__ __align__(1024) uint8_t smem_raw[];
  const uint32_t sb = smem_u32(smem_raw);
  const int warp = __shfl_sync(0xffffffff, threadIdx.x >> 5, 0);
  const int bid = __shfl_sync(0xffffffff, opaque(blockIdx.x), 0);
  int cb, r;
  {
    const int cl = bid >> 1;
    cb = cl >> 2; r = (cl & 3) * 2 + (bid & 1);
  }

  const int prof_id = cb * 8 + r; (void)prof_id;
  if (threadIdx.x == 0) {
    if (sb & 1023) __trap();
    for (int i = 0; i < 4; i++) { mbar_init(sb + B_BFULL + i * 8, 1); mbar_init(sb + B_BEMPTY + i * 8, 8); }
    for (int i = 0; i < 16; i++) mbar_init(sb + B_AFULL + i * 8, 1);
    for (int i = 0; i < 6; i++) { mbar_init(sb + B_AFREE + i * 8, 4); mbar_init(sb + B_OWN + i * 8, 4); }
    for (int i = 0; i < 2; i++) { mbar_init(sb + B_STAT + i * 8, 1); mbar_init(sb + B_PRDY + i * 8, 1); mbar_init(sb + B_PFREE + i * 8, 4); }
    mbar_init(sb + B_CSRDY, 1); mbar_init(sb + B_CSRDY + 8, 1); mbar_init(sb + B_KVDONE, 4); mbar_init(sb + B_KVRDY, 1);
    asm volatile("fence.mbarrier_init.release.cluster;" ::: "memory");
  }
  __syncthreads();
  asm volatile("barrier.cluster.arrive.relaxed.aligned;" ::: "memory");

  if (warp >= 8) {
  asm volatile("setmaxnreg.dec.sync.aligned.u32 96;");
  const int lane = __shfl_sync(0xffffffff, threadIdx.x & 31, threadIdx.x & 31);
  const uint32_t epoch = ld_relaxed(g_epoch + bid * 8);
  if (warp == 8) {
    uint32_t st = 0;
    auto acquire = [&](uint32_t bytes) -> uint32_t {
      const uint32_t s = st & 3;
      mbar_wait(sb + B_BEMPTY + s * 8, ((st >> 2) & 1) ^ 1);
      st++;
      return s;
    };
    if (lane == 0) { prefetch_map(&tm_wqkv); prefetch_map(&tm_wo); prefetch_map(&tm_w1); prefetch_map(&tm_w2); }
#pragma unroll 1
    for (int l = 0; l < 2; l++) {
#pragma unroll 1
      for (int i = 0; i < 8; i++) {
        const uint32_t s = acquire(0), dst = sb + SM_RING + s * SLOT, fb = sb + B_BFULL + s * 8;
        const int kc = (r + i) & 7;
        if (elect_one()) { mbar_expect_tx(fb, 16384); tma_load(dst, &tm_wqkv, 512 + 64 * r, 64 * kc, fb); tma_load(dst + 8192, &tm_wqkv, 1024 + 64 * r, 64 * kc, fb); }
      }
#pragma unroll 1
      for (int i = 0; i < 4; i++) {
        const uint32_t s = acquire(0), dst = sb + SM_RING + s * SLOT, fb = sb + B_BFULL + s * 8;
        if (elect_one()) { mbar_expect_tx(fb, 16384); tma_load(dst, &tm_wqkv, 64 * r, 64 * ((r + 2 * i) & 7), fb); tma_load(dst + 8192, &tm_wqkv, 64 * r, 64 * ((r + 2 * i + 1) & 7), fb); }
      }
#pragma unroll 1
      for (int i = 0; i < 4; i++) {
        const uint32_t s = acquire(0), dst = sb + SM_RING + s * SLOT, fb = sb + B_BFULL + s * 8;
        const int row = 64 * ((r + 2 * i) & 7);
        if (elect_one()) { mbar_expect_tx(fb, 16384); tma_load(dst, &tm_wo, 64 * (r ^ 1), row, fb); tma_load(dst + 8192, &tm_wo, 64 * r, row, fb); }
      }
#pragma unroll 1
      for (int i = 0; i < 8; i++) {
        const uint32_t s = acquire(0), dst = sb + SM_RING + s * SLOT, fb = sb + B_BFULL + s * 8;
        const int kc = (r + i) & 7;
        if (elect_one()) { mbar_expect_tx(fb, 24576); tma_load(dst, &tm_w1, kHS * r, 64 * kc, fb); tma_load(dst + 8192, &tm_w1, kHS * r + 64, 64 * kc, fb); tma_load(dst + 16384, &tm_w1, kHS * r + 128, 64 * kc, fb); }
      }
#pragma unroll 1
      for (int i = 0; i < 8; i++) {
        const uint32_t s = acquire(0), dst = sb + SM_RING + s * SLOT, fb = sb + B_BFULL + s * 8;
        const int col = i < 6 ? (r + 2 + 2 * (i % 3)) & 7 : r, sl = (i < 3 || i == 6) ? r : r ^ 1;
        if (elect_one()) { mbar_expect_tx(fb, kHS * 128); tma_load(dst, &tm_w2, 64 * col, kHS * sl, fb); }
      }
    }
    asm volatile("barrier.cluster.wait.aligned;" ::: "memory");
  } else if (warp == 9 || warp == 10) {
    const int h = warp - 9, half0 = cb * 2 + h;
    if (elect_one()) {
      const uint32_t abase = sb + h * 65536, afull = sb + B_AFULL + h * 64;
      prefetch_map(&tm_x);
      for (int i = 0; i < 8; i++) { mbar_expect_tx(afull + i * 8, 8192); tma_load(abase + i * 8192, &tm_x, 64 * ((r + i) & 7), 128 * cb + 64 * h, afull + i * 8); }
    }
    __syncwarp();
    const uint32_t ev0 = epoch * 16, tag = (epoch + 1) & 1;
    set_flags(g_flags + half0 * 128 + r * 2, ev0, lane);
    colsum_task(wqkv + (1 + h) * 512 + 64 * r + 8 * (lane & 7), 3 * kD, true, 32 * cb, g_cs + ((r * 2 + 0) * 16 + cb) * 48 + (1 + h) * 16 + 2 * (lane & 7), lane, tag);
    gather_stats(g_stats + (0 * 32 + half0) * 512, sb + SM_STAT + h * 512, sb + B_STAT + h * 8, lane, tag);
#pragma unroll 1
    for (int b = h; b < 3; b += 2) {
      const int col = 64 * b + 8 * (lane & 7);
      colsum_task(w1 + kHS * r + col, kFF, col < kHS && kHS * r + col < kFF, 32 * cb, g_cs + ((r * 2 + 1) * 16 + cb) * 48 + b * 16 + 2 * (lane & 7), lane, tag);
    }
    asm volatile("barrier.cluster.wait.aligned;" ::: "memory");
    uint32_t p0 = 0;
#pragma unroll 1
    for (int l = 0; l < 2; l++) {
      const uint32_t ev = ev0 + l * 6;
      const int half = opaque(half0);
      const uint32_t abase = sb + h * 65536, afull = sb + B_AFULL + h * 64, afree = sb + B_AFREE + h * 24, own = sb + B_OWN + h * 24;
      uint4* flags = g_flags + half * 128;
      mbar_wait(own, p0);
      STAMP(2 + h, l * 16 + 0);
      publish_chunk(g_act + (0 * 32 + half) * 4096 + r * 512, abase, flags + r * 2, ev + 1, lane);
      STAMP(2 + h, l * 16 + 11);
      mbar_wait(afree, p0); p0 ^= 1;
      fetch_chunks<4, 2>(g_act + (0 * 32 + half) * 4096, flags, abase, afull, r, ev + 1, lane);
      STAMP(2 + h, l * 16 + 1);
      mbar_wait(own, p0);
      STAMP(2 + h, l * 16 + 2);
      publish_chunk(g_act + (1 * 32 + half) * 4096 + r * 512, abase, flags + r * 2, ev + 2, lane);
      mbar_wait(afree, p0); p0 ^= 1;
      STAMP(2 + h, l * 16 + 12);
      fetch_chunks<8, 1>(g_act + (1 * 32 + half) * 4096, flags, abase, afull, r, ev + 2, lane);
      STAMP(2 + h, l * 16 + 4);
      gather_stats(g_stats + ((2 * l + 1) * 32 + half) * 512, sb + SM_STAT + h * 512, sb + B_STAT + h * 8, lane, tag);
      STAMP(2 + h, l * 16 + 3);
      mbar_wait(afree, p0);
      if (lane < 3) mbar_expect_tx(afull + (1 + lane) * 8, lane == 2 ? 6144 : 8192);
      mbar_wait(afree + 8, l);
      STAMP(2 + h, l * 16 + 5);
      {
        const uint32_t pdst = mapa(abase + 24576, (r & 1) ^ 1), pbar = mapa(afull + 8, (r & 1) ^ 1);
        mbar_wait(own, p0); p0 ^= 1;
        if (lane == 0) bulk_s2peer(pdst, abase, 8192, pbar);
        mbar_wait(own + 8, l);
        if (lane == 0) bulk_s2peer(pdst + 8192, abase + 8192, 8192, pbar + 8);
        mbar_wait(own + 16, l);
        if (lane == 0) bulk_s2peer(pdst + 16384, abase + 16384, 6144, pbar + 16);
      }
      STAMP(2 + h, l * 16 + 6);
      mbar_wait(own, p0);
      STAMP(2 + h, l * 16 + 8);
      if (l == 0) {
        publish_chunk(g_act + (2 * 32 + half) * 4096 + r * 512, abase, flags + r * 2, ev + 6, lane);
        mbar_wait(afree, p0); p0 ^= 1;
        fetch_chunks<8, 1>(g_act + (2 * 32 + half) * 4096, flags, abase, afull, r, ev + 6, lane);
        STAMP(2 + h, l * 16 + 9);
        gather_stats(g_stats + (2 * 32 + half) * 512, sb + SM_STAT + h * 512, sb + B_STAT + h * 8, lane, tag);
      } else if (lane == 0) {
        tma_store(&tm_out, abase, 64 * r, 128 * cb + 64 * h); bulk_commit(); bulk_wait<0>();
      }
      STAMP(2 + h, l * 16 + 10);
    }
  } else {
    if (lane < 24) { g_kv[(0 * 8 + r) * 384 + cb * 24 + lane] = make_float4(0.f, 0.f, 0.f, 0.f); g_kv[(1 * 8 + r) * 384 + cb * 24 + lane] = make_float4(0.f, 0.f, 0.f, 0.f); }
    fence_gpu();
    const uint32_t tag = (epoch & 1) ^ 1;
    colsum_task(wqkv + 64 * r + 8 * (lane & 7), 3 * kD, true, 32 * cb, g_cs + ((r * 2 + 0) * 16 + cb) * 48 + 2 * (lane & 7), lane, tag);
    __nanosleep(500);
    colsum_gather(g_cs + (r * 2 + 0) * 16 * 48, sb + SM_CS, 48, lane, tag);
    fence_gpu();
    if (lane == 0) mbar_arrive(sb + B_CSRDY);
    STAMP(2, 48);
    if (lane == 1) prefetch_l2((const char*)wo + bid * 4096, 4096);
    if (lane == 2) prefetch_l2((const char*)w2 + bid * 11008, 11008);
    asm volatile("barrier.cluster.wait.aligned;" ::: "memory");
#pragma unroll 1
    for (int l = 0; l < 2; l++) {
      mbar_wait(sb + B_KVDONE, l);
      STAMP(2, 50 + l * 4);
      const float4* kv = g_kv + (l * 8 + r) * 384 + lane;
      float4 v[12];
      uint32_t cnt = 0;
      __nanosleep(KVDELAY);
      {
        const float4* pp = g_kv + (l * 8 + r) * 384 + (lane & 3) * 96 + 95;
        while (!__all_sync(0xffffffff, ld_relaxed_f4(pp).w == 16.f)) { if (++cnt > SPIN_LIMIT) __trap(); __nanosleep(KVSLEEP); }
      }
      STAMP(2, 51 + l * 4);
      while (true) {
        bool ok = true;
#pragma unroll
        for (int i = 0; i < 12; i++) v[i] = ld_relaxed_f4(kv + i * 32);
#pragma unroll
        for (int i = 0; i < 12; i++) ok = ok && v[i].w == 16.f;
        if (__all_sync(0xffffffff, ok)) break;
        if (++cnt > SPIN_LIMIT) __trap();
      }
      STAMP(2, 52 + l * 4);
#pragma unroll
      for (int hh = 0; hh < 4; hh++) {
        const float4 a = v[3 * hh], b = v[3 * hh + 1], c = v[3 * hh + 2];
        const float z0 = __shfl_sync(0xffffffff, c.z, lane & 3), z1 = __shfl_sync(0xffffffff, c.z, 4 + (lane & 3)),
                    z2 = __shfl_sync(0xffffffff, c.z, 8 + (lane & 3)), z3 = __shfl_sync(0xffffffff, c.z, 12 + (lane & 3));
        const uint32_t d = sb + SM_RING + 16384 + hh * 768 + lane * 8;
        sts_u2(d, pack_bf16(a.x, a.y), pack_bf16(a.z, b.x));
        sts_u2(d + 256, pack_bf16(b.y, b.z), pack_bf16(c.x, c.y));
        sts_u2(d + 512, pack_bf16(z0, z1), pack_bf16(z2, z3));
      }
      __syncwarp();
      if (lane == 0) mbar_arrive(sb + B_KVRDY);
      STAMP(2, 53 + l * 4);
      if (l == 0) {
        colsum_gather(g_cs + (r * 2 + 1) * 16 * 48, sb + SM_CS + 768, 44, lane, tag);
        if (lane == 0) mbar_arrive(sb + B_CSRDY + 8);
      }
    }
    if (lane == 0) g_epoch[bid * 8] = epoch + 1;
  }
  } else {
    asm volatile("setmaxnreg.inc.sync.aligned.u32 200;");
    const int lane = __shfl_sync(0xffffffff, threadIdx.x & 31, threadIdx.x & 31);
    const uint32_t epoch = ld_relaxed(g_epoch + bid * 8);
    const int wg0 = warp >> 2, lane0 = lane, half = cb * 2 + wg0, wg = wg0;
    const uint32_t sb0 = sb;
    STAMP(wg, 62);
    const uint32_t tag = (epoch + 1) & 1;
    uint32_t xr[16];
    uint32_t sph = 0;
    mbar_wait(sb0 + B_AFULL + wg0 * 64, 0);
#pragma unroll
    for (int s = 0; s < 4; s++)
      ldsm4(sb0 + wg0 * 65536 + (16 * (warp & 3) + 8 * ((lane0 >> 3) & 1) + (lane0 & 7)) * 128 + (((2 * s + (lane0 >> 4)) ^ (lane0 & 7)) << 4),
            xr[4 * s], xr[4 * s + 1], xr[4 * s + 2], xr[4 * s + 3]);
    asm volatile("barrier.cluster.wait.aligned;" ::: "memory");
    if (DELTA0 && wg0 == 1) spin(DELTA0);
    STAMP(wg, 63);

#pragma unroll 1
    for (int l = 0; l < 2; l++) {
      const uint32_t sb = opaque(sb0);
      const int lane = opaque(lane0), wg = opaque(wg0), wq = opaque(warp) & 3, g = lane >> 2, t = lane & 3;
      const uint32_t abase = sb + wg * 65536, afull = sb + B_AFULL + wg * 64, afree = sb + B_AFREE + wg * 24, own = sb + B_OWN + wg * 24;
      const uint32_t ring = sb + SM_RING;
      const uint32_t dA = desc_lo(abase, 16), dH = desc_lo(abase, 1024), dB = desc_lo(ring, 8192);
      constexpr int S4 = SLOT >> 4;
      uint32_t swa[4];
#pragma unroll
      for (int s = 0; s < 4; s++) swa[s] = abase + (16 * wq + 8 * ((lane >> 3) & 1) + (lane & 7)) * 128 + (((2 * s + (lane >> 4)) ^ (lane & 7)) << 4);
      auto wait_b = [&](int st) { mbar_wait(sb + B_BFULL + (st & 3) * 8, (st >> 2) & 1); };
      auto release_b = [&](int st) { if (lane == 0) mbar_arrive(sb + B_BEMPTY + (st & 3) * 8); };
      auto signal = [&](uint32_t bar) { __syncwarp(); if (lane == 0) mbar_arrive(bar); };
      const uint32_t chk = abase + (16 * wq + g) * 128 + (((2 * t) ^ g) << 4);
      auto bad_chunk = [&](int i, uint32_t tg) -> uint32_t { return (lds_u32(chk + i * 8192) ^ tg) | (lds_u32(chk + (i * 8192 + 1024)) ^ tg); };
      auto apar = [&](int i, int ph) -> uint32_t { return (i < 4 || ph == 0 ? ph : ph - 1) & 1; };
      auto fetch_ok = [&](int i, int n, int ph, int str, int buf, uint32_t tg) {
        uint32_t bad = 0;
#pragma unroll
        for (int u = i; u < i + n; u++) mbar_wait(afull + u * 8, apar(u, ph));
#pragma unroll
        for (int u = i; u < i + n; u++) bad |= bad_chunk(u, tg);
        if (__builtin_expect(!__all_sync(0xffffffff, (bad & 1u) == 0), 0)) {
#pragma unroll 1
          for (int u = i; u < i + n; u++) {
            const uint4* src = g_act + (buf * 32 + opaque(half)) * 4096 + ((opaque(r) + str * u) & 7) * 512 + wq * 128 + opaque(lane);
            const uint32_t dst = abase + u * 8192 + wq * 2048 + opaque(lane) * 16;
            uint32_t cnt = 0;
            while (!__all_sync(0xffffffff, (bad_chunk(u, tg) & 1u) == 0)) {
#pragma unroll 1
              for (int v = 0; v < 4; v++) sts_u4(dst + v * 512, ld_relaxed_u4(src + v * 32));
              fence_async_smem();
              __syncwarp();
              HEALCNT();
              if (++cnt > SPIN_LIMIT) __trap();
            }
          }
        }
      };
      auto peer_ready = [&]() {
        if (lane == 0) { mbar_arrive_remote(mapa(sb + B_PFREE + wg * 8, (r & 1) ^ 1)); if (wq == 0) mbar_expect_tx(sb + B_PRDY + wg * 8, 8192); }
      };
      auto send_partial = [&](const float (&v)[32], uint32_t land, uint32_t par) {
        mbar_wait(sb + B_PFREE + wg * 8, par);
        const uint32_t rdst = mapa(abase + land + (wq * 32 + lane) * 16, (r & 1) ^ 1), rbar = mapa(sb + B_PRDY + wg * 8, (r & 1) ^ 1);
#pragma unroll
        for (int i = 0; i < 4; i++)
          st_async_v4(rdst + i * 2048, pack_bf16(v[8 * i], v[8 * i + 1]), pack_bf16(v[8 * i + 2], v[8 * i + 3]),
                      pack_bf16(v[8 * i + 4], v[8 * i + 5]), pack_bf16(v[8 * i + 6], v[8 * i + 7]), rbar);
      };
      auto add_residual = [&](const float (&v)[32], uint32_t land, uint32_t par) {
        const float a0 = 1.f, a1 = 1.f;
        mbar_wait(sb + B_PRDY + wg * 8, par);
        uint4 p[4];
#pragma unroll
        for (int i = 0; i < 4; i++) p[i] = lds_u4(abase + land + i * 2048 + (wq * 32 + lane) * 16);
#pragma unroll
        for (int i = 0; i < 4; i++) {
          xr[4 * i] = pack_bf16(fmaf(a0, v[8 * i] + bf_lo(p[i].x), bf_lo(xr[4 * i])), fmaf(a0, v[8 * i + 1] + bf_hi(p[i].x), bf_hi(xr[4 * i])));
          xr[4 * i + 1] = pack_bf16(fmaf(a1, v[8 * i + 2] + bf_lo(p[i].y), bf_lo(xr[4 * i + 1])), fmaf(a1, v[8 * i + 3] + bf_hi(p[i].y), bf_hi(xr[4 * i + 1])));
          xr[4 * i + 2] = pack_bf16(fmaf(a0, v[8 * i + 4] + bf_lo(p[i].z), bf_lo(xr[4 * i + 2])), fmaf(a0, v[8 * i + 5] + bf_hi(p[i].z), bf_hi(xr[4 * i + 2])));
          xr[4 * i + 3] = pack_bf16(fmaf(a1, v[8 * i + 6] + bf_lo(p[i].w), bf_lo(xr[4 * i + 3])), fmaf(a1, v[8 * i + 7] + bf_hi(p[i].w), bf_hi(xr[4 * i + 3])));
        }
      };
      const uint32_t tmask = t == 0 ? 1u : 0u;
      auto store_chunk = [&](const uint32_t (&v)[16], uint32_t tg  , uint32_t msk) {
#pragma unroll
        for (int s = 0; s < 4; s++) stsm4(swa[s], (v[4 * s] & ~msk) | tg, (v[4 * s + 1] & ~msk) | tg, v[4 * s + 2], v[4 * s + 3]);
        fence_async_smem();
        signal(own);
      };
      auto stat_dst = [&](int ln) -> float2* { return g_stats + (ln * 32 + opaque(half)) * 512 + opaque(r) * 64 + 16 * wq + g; };
      const uint32_t stat_sm = sb + SM_STAT + (wg * 64 + 16 * wq + g) * 8;
      const uint32_t cs_sm = sb + SM_CS + 8 * t;
      const uint32_t ltag = l ^ 1;
      float rs0, rs1;
      {
        float ak[32], av[32], aq[32];
        STAMP(wg, l * 24 + 0);
        {
          wait_b(0);
          wg_fence();
          wgmma_n128_init<0, 0, HI_SW>(ak, av, dA, dB);
          static_for<1, 4>([&](auto K) { wgmma_n128<2 * K.value, 128 * K.value, HI_SW>(ak, av, dA, dB); });
          wg_commit();
          publish_stats(xr, stat_dst(2 * l), t, tag);
        }
        static_for<1, 8>([&](auto I) {
          constexpr int i = I.value;
          if (l == 0) mbar_wait(afull + i * 8, 0); else fetch_ok(i, 1, 0, 1, 2, tag);
          if (i == 1) STAMP(wg, l * 2 + 19);
          wait_b(i);
          wg_fence_in();
          static_for<0, 4>([&](auto K) { wgmma_n128<i * 512 + 2 * K.value, (i & 3) * S4 + 128 * K.value, HI_SW>(ak, av, dA, dB); });
          wg_commit();
          wg_wait<1>(); release_b(i - 1);
        });
        STAMP(wg, l * 24 + 1);
        auto q_stage = [&](auto I) {
          constexpr int i = I.value;
          wait_b(8 + i);
          wg_fence();
          static_for<0, 8>([&](auto K) {
            constexpr int k = K.value;
            if constexpr (i == 0 && k == 0) wgmma_n64_init<0, 0, HI_SW>(aq, dA, dB);
            else wgmma_n64<i * 1024 + (k >> 2) * 512 + 2 * (k & 3), i * S4 + 128 * k, HI_SW>(aq, dA, dB);
          });
          wg_commit();
        };
        if (l == 0) mbar_wait(sb + B_CSRDY, 0);
        mbar_wait(sb + B_STAT + wg * 8, sph); sph ^= 1;
        const float2 s0 = lds_f2(stat_sm), s1 = lds_f2(stat_sm + 64);
        const float y0 = s0.x * 1.4426950408889634f, y1 = s1.x * 1.4426950408889634f;
        const uint32_t pk_s = ring + (2 * wg) * SLOT + 16384;
        {
          float2 c[16];
#pragma unroll
          for (int j = 0; j < 16; j++) c[j] = lds_f2(cs_sm + (64 + 8 * j) * 4);
          wg_wait<0>(); release_b(7);
          fence_regs(ak); fence_regs(av);
          STAMP(wg, l * 24 + 2);
          uint32_t pk[16], pv[16];
#pragma unroll
          for (int j = 0; j < 8; j++) {
            pk[2 * j] = pack_bf16(phi_y(y0 * fmaf(s0.y, c[j].x, ak[4 * j])), phi_y(y0 * fmaf(s0.y, c[j].y, ak[4 * j + 1])));
            pk[2 * j + 1] = pack_bf16(phi_y(y1 * fmaf(s1.y, c[j].x, ak[4 * j + 2])), phi_y(y1 * fmaf(s1.y, c[j].y, ak[4 * j + 3])));
            pv[2 * j] = pack_bf16(s0.x * fmaf(s0.y, c[8 + j].x, av[4 * j]), s0.x * fmaf(s0.y, c[8 + j].y, av[4 * j + 1]));
            pv[2 * j + 1] = pack_bf16(s1.x * fmaf(s1.y, c[8 + j].x, av[4 * j + 2]), s1.x * fmaf(s1.y, c[8 + j].y, av[4 * j + 3]));
          }
#pragma unroll
          for (int s = 0; s < 4; s++) {
            stsm4(swa[s] + (pk_s - abase), pk[4 * s], pk[4 * s + 1], pk[4 * s + 2], pk[4 * s + 3]);
            stsm4(swa[s] + (pk_s - abase) + SLOT, pv[4 * s], pv[4 * s + 1], pv[4 * s + 2], pv[4 * s + 3]);
          }
        }
        STAMP(wg, 20 + l * 2);
        if (wg == 0) { asm volatile("bar.arrive 4, 256;" ::: "memory"); if (QWAIT) asm volatile("bar.sync 5, 256;" ::: "memory"); }
        else {
          asm volatile("bar.sync 4, 256;" ::: "memory");
          float c0[4] = {0.f, 0.f, 0.f, 0.f}, c1[4] = {0.f, 0.f, 0.f, 0.f}, z0[4] = {0.f, 0.f, 0.f, 0.f}, z1[4] = {0.f, 0.f, 0.f, 0.f};
          const int m = lane >> 3;
          const uint32_t va = ring + SLOT + 16384 + (8 * (m >> 1) + (lane & 7)) * 128 + (((2 * wq + (m & 1)) ^ (lane & 7)) << 4);
          const uint32_t pa = ring + 16384 + (8 * (m & 1) + (lane & 7)) * 128 + (((2 * wq + (m >> 1)) ^ (lane & 7)) << 4);
#pragma unroll
          for (int ks = 0; ks < 8; ks++) {
            uint32_t a0, a1, a2, a3, b0, b1, b2, b3;
            ldsm4t(va + (ks >> 2) * 2 * SLOT + (ks & 3) * 2048, a0, a1, a2, a3);
            ldsm4t(pa + (ks >> 2) * 2 * SLOT + (ks & 3) * 2048, b0, b1, b2, b3);
            mma16816(c0, a0, a1, a2, a3, b0, b1);
            mma16816(c1, a0, a1, a2, a3, b2, b3);
            mma16816(z0, 0x3f803f80u, 0x3f803f80u, 0x3f803f80u, 0x3f803f80u, b0, b1);
            mma16816(z1, 0x3f803f80u, 0x3f803f80u, 0x3f803f80u, 0x3f803f80u, b2, b3);
          }
          if (QWAIT) asm volatile("bar.arrive 5, 256;" ::: "memory");
          float* kv = (float*)(g_kv + (l * 8 + opaque(r)) * 384 + wq * 96 + lane);
          red_add_f4(kv, c0[0], c0[1], c1[0], 1.f);
          red_add_f4(kv + 128, c1[1], c0[2], c0[3], 1.f);
          red_add_f4(kv + 256, c1[2], c1[3], g == 0 ? z0[0] : g == 1 ? z0[1] : g == 2 ? z1[0] : z1[1], 1.f);
          signal(sb + B_KVDONE);
        }
        STAMP(wg, l * 24 + 3);
        q_stage(IC<0>{}); q_stage(IC<1>{}); q_stage(IC<2>{}); q_stage(IC<3>{});
        float2 c[8];
#pragma unroll
        for (int j = 0; j < 8; j++) c[j] = lds_f2(cs_sm + 8 * j * 4);
        wg_wait<3>(); release_b(8);
        wg_wait<2>(); release_b(9);
        wg_wait<1>(); release_b(10);
        wg_wait<0>(); release_b(11);
        fence_regs(aq);
        if (lane == 0) mbar_arrive(afree);
        peer_ready();
        STAMP(wg, l * 24 + 4);
        uint32_t pq[16];
#pragma unroll
        for (int j = 0; j < 8; j++) {
          pq[2 * j] = pack_bf16(phi_y(y0 * fmaf(s0.y, c[j].x, aq[4 * j])), phi_y(y0 * fmaf(s0.y, c[j].y, aq[4 * j + 1])));
          pq[2 * j + 1] = pack_bf16(phi_y(y1 * fmaf(s1.y, c[j].x, aq[4 * j + 2])), phi_y(y1 * fmaf(s1.y, c[j].y, aq[4 * j + 3])));
        }
        STAMP(wg, l * 24 + 5);
        mbar_wait(sb + B_KVRDY, l);
        if (DELTA && wg == 1) spin(DELTA);
        STAMP(wg, l * 24 + 6);
        uint2 f[12];
#pragma unroll
        for (int i = 0; i < 12; i++) f[i] = lds_u2(ring + 16384 + i * 256 + lane * 8);
        float cn[4][8], cz[4][4];
#pragma unroll
        for (int hh = 0; hh < 4; hh++) {
          float c0[4] = {0.f, 0.f, 0.f, 0.f}, c1[4] = {0.f, 0.f, 0.f, 0.f};
          cz[hh][0] = cz[hh][1] = cz[hh][2] = cz[hh][3] = 0.f;
          mma16816(cz[hh], pq[4 * hh], pq[4 * hh + 1], pq[4 * hh + 2], pq[4 * hh + 3], f[3 * hh + 2].x, f[3 * hh + 2].y);
          mma16816(c0, pq[4 * hh], pq[4 * hh + 1], pq[4 * hh + 2], pq[4 * hh + 3], f[3 * hh].x, f[3 * hh].y);
          mma16816(c1, pq[4 * hh], pq[4 * hh + 1], pq[4 * hh + 2], pq[4 * hh + 3], f[3 * hh + 1].x, f[3 * hh + 1].y);
#pragma unroll
          for (int u = 0; u < 4; u++) { cn[hh][u] = c0[u]; cn[hh][4 + u] = c1[u]; }
        }
        uint32_t o[16];
#pragma unroll
        for (int hh = 0; hh < 4; hh++) {
          const float i0 = rcp(cz[hh][0] + 1e-6f), i1 = rcp(cz[hh][2] + 1e-6f);
          o[4 * hh] = pack_bf16(cn[hh][0] * i0, cn[hh][1] * i0); o[4 * hh + 1] = pack_bf16(cn[hh][2] * i1, cn[hh][3] * i1);
          o[4 * hh + 2] = pack_bf16(cn[hh][4] * i0, cn[hh][5] * i0); o[4 * hh + 3] = pack_bf16(cn[hh][6] * i1, cn[hh][7] * i1);
        }
        store_chunk(o, ltag & tmask, tmask);
        wg_bar(wg);
        STAMP(wg, l * 24 + 7);
      }
      {
        float ap[32], ao[32];
        wait_b(12);
        wg_fence();
        wgmma_n64_init<0, 0, HI_SW>(ap, dA, dB);
        static_for<1, 4>([&](auto K) { wgmma_n64<2 * K.value, 128 * K.value, HI_SW>(ap, dA, dB); });
        wgmma_n64_init<0, 512, HI_SW>(ao, dA, dB);
        static_for<1, 4>([&](auto K) { wgmma_n64<2 * K.value, 512 + 128 * K.value, HI_SW>(ao, dA, dB); });
        wg_commit();
        wait_b(13);
        wg_wait<0>(); release_b(12);
        fetch_ok(1, 1, 1, 2, 0, ltag);
        STAMP(wg, l * 24 + 8);
        wg_fence();
        static_for<0, 4>([&](auto K) { wgmma_n64<512 + 2 * K.value, S4 + 128 * K.value, HI_SW>(ap, dA, dB); });
        static_for<0, 4>([&](auto K) { wgmma_n64<512 + 2 * K.value, S4 + 512 + 128 * K.value, HI_SW>(ao, dA, dB); });
        wg_commit();
        wait_b(14); wait_b(15);
        wg_wait<0>(); release_b(13);
        static_for<2, 4>([&](auto I) {
          constexpr int i = I.value;
          fetch_ok(i, 1, 1, 2, 0, ltag);
          if (l == 1) STAMP(wg, 43 + i);
          wg_fence();
          static_for<0, 4>([&](auto K) { wgmma_n64<i * 512 + 2 * K.value, i * S4 + 128 * K.value, HI_SW>(ap, dA, dB); });
        });
        wg_commit();
        static_for<0, 8>([&](auto K) { wgmma_n64<(2 + K.value / 4) * 512 + 2 * (K.value & 3), (2 + K.value / 4) * S4 + 512 + 128 * (K.value & 3), HI_SW>(ao, dA, dB); });
        wg_commit();
        wg_wait<1>();
        fence_regs(ap);
        send_partial(ap, 4 * 8192, l);
        wg_wait<0>(); release_b(14); release_b(15);
        fence_regs(ao);
        STAMP(wg, l * 24 + 9);
        add_residual(ao, 4 * 8192, l);
        signal(afree);
        store_chunk(xr, ltag & tmask, tmask);
        wg_bar(wg);
        STAMP(wg, l * 24 + 10);
      }
      {
        float acc[88];
        {
          wait_b(16);
          wg_fence();
          wgmma_n176_init<0, 0, HI_SW>(acc, dA, dB);
          static_for<1, 4>([&](auto K) { wgmma_n176<2 * K.value, 128 * K.value, HI_SW>(acc, dA, dB); });
          wg_commit();
          publish_stats(xr, stat_dst(2 * l + 1), t, tag);
        }
        static_for<1, 8>([&](auto I) {
          constexpr int i = I.value;
          fetch_ok(i, 1, 2, 1, 1, ltag);
          if (i == 1) STAMP(wg, l * 24 + 11);
          wait_b(16 + i);
          wg_fence_in();
          static_for<0, 4>([&](auto K) { wgmma_n176<i * 512 + 2 * K.value, (i & 3) * S4 + 128 * K.value, HI_SW>(acc, dA, dB); });
          wg_commit();
          wg_wait<1>(); release_b(15 + i);
        });
        if (l == 0) mbar_wait(sb + B_CSRDY + 8, 0);
        mbar_wait(sb + B_STAT + wg * 8, sph); sph ^= 1;
        const float2 s0 = lds_f2(stat_sm), s1 = lds_f2(stat_sm + 64);
        float2 c[22];
#pragma unroll
        for (int j = 0; j < 22; j++) c[j] = lds_f2(cs_sm + (192 + 8 * j) * 4);
        rs0 = s0.x; rs1 = s1.x;
        wg_wait<0>(); release_b(23);
        fence_regs(acc);
        if (lane == 0) { mbar_arrive(afree); mbar_arrive_remote(mapa(afree + 8, (r & 1) ^ 1)); }
        STAMP(wg, l * 24 + 12);
        const uint32_t hrow = abase + (lane >> 4) * 1024 + (2 * wq + ((lane >> 3) & 1)) * 128 + (lane & 7) * 16;
        wg_bar(wg);
#pragma unroll
        for (int b = 0; b < 3; b++) {
          uint32_t p[16];
#pragma unroll
          for (int u = 0; u < (b == 2 ? 6 : 8); u++) {
            const int j = 8 * b + u;
            p[2 * u] = pack_bf16_relu(fmaf(s0.y, c[j].x, acc[4 * j]), fmaf(s0.y, c[j].y, acc[4 * j + 1]));
            p[2 * u + 1] = pack_bf16_relu(fmaf(s1.y, c[j].x, acc[4 * j + 2]), fmaf(s1.y, c[j].y, acc[4 * j + 3]));
          }
#pragma unroll
          for (int s = 0; s < (b == 2 ? 3 : 4); s++) stsm4(hrow + (4 * b + s) * 2048, p[4 * s], p[4 * s + 1], p[4 * s + 2], p[4 * s + 3]);
          fence_async_smem(); signal(own + b * 8);
        }
        wg_bar(wg);
        STAMP(wg, l * 24 + 13);
      }
      {
        float a1[32], a2[32], a3[32], a0[32];
        auto part = [&](float (&acc)[32], auto ST, auto PEER, auto INIT) {
          constexpr int st = ST.value, oa = PEER.value * 1536, ob = (st & 3) * S4;
          wait_b(st);
          wg_fence();
          static_for<0, 11>([&](auto K) {
            if (st == 27 && (K.value & 3) == 0) mbar_wait(afull + (1 + K.value / 4) * 8, 1);
            if constexpr (INIT.value && K.value == 0) wgmma_n64_init<oa, ob, HI_NS>(acc, dH, dB);
            else wgmma_n64<oa + 128 * K.value, ob + 128 * K.value, HI_NS>(acc, dH, dB);
          });
          wg_commit();
        };
        auto send = [&](const float (&v)[32], int i) {
          uint4* dst = g_part + ((opaque(half) * 8 + ((opaque(r) + 2 * i) & 7)) * 3 + 3 - i) * 512 + wq * 128 + lane;
#pragma unroll
          for (int u = 0; u < 4; u++)
            st_relaxed_u4(dst + u * 32, make_uint4((pack_bf16(v[8 * u], v[8 * u + 1]) & ~1u) | ltag, pack_bf16(v[8 * u + 2], v[8 * u + 3]),
                                                   pack_bf16(v[8 * u + 4], v[8 * u + 5]), pack_bf16(v[8 * u + 6], v[8 * u + 7])));
        };
        part(a1, IC<24>{}, IC<0>{}, IC<1>{});
        part(a2, IC<25>{}, IC<0>{}, IC<1>{});
        wg_wait<1>(); release_b(24);
        part(a3, IC<26>{}, IC<0>{}, IC<1>{});
        wg_wait<1>(); release_b(25);
        if (l == 1) STAMP(wg, 51);
        part(a1, IC<27>{}, IC<1>{}, IC<0>{});
        if (lane == 0) mbar_arrive_remote(mapa(afree + 16, (r & 1) ^ 1));
        STAMP(wg, l * 24 + 14);
        wg_wait<1>(); release_b(26);
        part(a2, IC<28>{}, IC<1>{}, IC<0>{});
        wg_wait<1>(); release_b(27);
        fence_regs(a1);
        send(a1, 1);
        if (l == 1) STAMP(wg, 52);
        part(a3, IC<29>{}, IC<1>{}, IC<0>{});
        wg_wait<1>(); release_b(28);
        fence_regs(a2);
        send(a2, 2);
        if (l == 1) STAMP(wg, 53);
        part(a0, IC<30>{}, IC<0>{}, IC<1>{});
        wg_wait<1>(); release_b(29);
        fence_regs(a3);
        send(a3, 3);
        if (l == 1) STAMP(wg, 54);
        part(a0, IC<31>{}, IC<1>{}, IC<0>{});
        STAMP(wg, l * 24 + 15);
        float sum[32];
        {
          const uint4* src = g_part + (opaque(half) * 8 + opaque(r)) * 3 * 512 + wq * 128 + lane;
#pragma unroll
          for (int i = 2; i >= 0; i--) {
            uint4 p[4];
            uint32_t cnt = 0;
            while (true) {
#pragma unroll
              for (int u = 0; u < 4; u++) p[u] = ld_relaxed_u4(src + i * 512 + u * 32);
              if (__all_sync(0xffffffff, ((((p[0].x ^ ltag) | (p[1].x ^ ltag)) | ((p[2].x ^ ltag) | (p[3].x ^ ltag))) & 1u) == 0)) break;
              if (++cnt > SPIN_LIMIT) __trap();
            }
#pragma unroll
            for (int u = 0; u < 4; u++) {
              const float w[8] = {bf_lo(p[u].x), bf_hi(p[u].x), bf_lo(p[u].y), bf_hi(p[u].y), bf_lo(p[u].z), bf_hi(p[u].z), bf_lo(p[u].w), bf_hi(p[u].w)};
#pragma unroll
              for (int v = 0; v < 8; v++) sum[8 * u + v] = i == 2 ? w[v] : sum[8 * u + v] + w[v];
            }
            if (l == 1) STAMP(wg, 57 - i);
          }
        }
        STAMP(wg, l * 24 + 16);
        wg_wait<1>(); release_b(30);
        wg_wait<0>(); release_b(31);
        fence_regs(a0);
        mbar_wait(afree + 16, l);
        wg_bar(wg);
#pragma unroll
        for (int j = 0; j < 8; j++) {
          xr[2 * j] = pack_bf16(fmaf(rs0, a0[4 * j] + sum[4 * j], bf_lo(xr[2 * j])), fmaf(rs0, a0[4 * j + 1] + sum[4 * j + 1], bf_hi(xr[2 * j])));
          xr[2 * j + 1] = pack_bf16(fmaf(rs1, a0[4 * j + 2] + sum[4 * j + 2], bf_lo(xr[2 * j + 1])), fmaf(rs1, a0[4 * j + 3] + sum[4 * j + 3], bf_hi(xr[2 * j + 1])));
        }
        STAMP(wg, l * 24 + 17);
        {
          signal(afree);
          store_chunk(xr, l == 0 ? (tag & tmask) : 0u, l == 0 ? tmask : 0u);
          wg_bar(wg);
          STAMP(wg, l * 24 + 18);
        }
      }
      if (l == 0) asm volatile("" ::: "memory");
    }

  }
}

typedef CUresult (*EncodeFn)(CUtensorMap*, CUtensorMapDataType, cuuint32_t, void*, const cuuint64_t*, const cuuint64_t*, const cuuint32_t*,
                             const cuuint32_t*, CUtensorMapInterleave, CUtensorMapSwizzle, CUtensorMapL2promotion, CUtensorMapFloatOOBfill);

CUtensorMap make_map(EncodeFn enc, const void* ptr, uint64_t cols, uint64_t rows, uint32_t box_rows) {
  CUtensorMap m;
  cuuint64_t gd[2] = {cols, rows}, gs[1] = {cols * 2};
  cuuint32_t bd[2] = {64, box_rows}, es[2] = {1, 1};
  enc(&m, CU_TENSOR_MAP_DATA_TYPE_BFLOAT16, 2, const_cast<void*>(ptr), gd, gs, bd, es, CU_TENSOR_MAP_INTERLEAVE_NONE,
      CU_TENSOR_MAP_SWIZZLE_128B, CU_TENSOR_MAP_L2_PROMOTION_L2_128B, CU_TENSOR_MAP_FLOAT_OOB_FILL_NONE);
  return m;
}

}

extern "C" void kernel_launch(void* const* d_in, const int* in_sizes, int n_in, void* d_out, int out_size) {
  (void)in_sizes; (void)n_in; (void)out_size;
  const __nv_bfloat16* x = (const __nv_bfloat16*)d_in[0];
  const __nv_bfloat16* wqkv = (const __nv_bfloat16*)d_in[1];
  const __nv_bfloat16* wo = (const __nv_bfloat16*)d_in[2];
  const __nv_bfloat16* w1 = (const __nv_bfloat16*)d_in[4];
  const __nv_bfloat16* w2 = (const __nv_bfloat16*)d_in[5];
  void* fn = nullptr;
  cudaDriverEntryPointQueryResult q;
  cudaGetDriverEntryPoint("cuTensorMapEncodeTiled", &fn, cudaEnableDefault, &q);
  EncodeFn enc = (EncodeFn)fn;
  const CUtensorMap tm_x = make_map(enc, x, kD, kS, 64), tm_out = make_map(enc, d_out, kD, kS, 64),
                    tm_wqkv = make_map(enc, wqkv, 3 * kD, kD, 64), tm_wo = make_map(enc, wo, kD, kD, 64),
                    tm_w1 = make_map(enc, w1, kFF, kD, 64), tm_w2 = make_map(enc, w2, kD, kFF, kHS);
  cudaFuncSetAttribute(fused_kernel, cudaFuncAttributeMaxDynamicSharedMemorySize, SM_TOTAL);
  fused_kernel<<<128, 384, SM_TOTAL>>>(tm_x, tm_out, tm_wqkv, tm_wo, tm_w1, tm_w2, wqkv, wo, w1, w2);
}
```

```cpp
#include <cuda_runtime.h>
#include <cuda_bf16.h>
#include <cuda.h>
#include <stdint.h>

namespace {

constexpr int kS = 2048, kD = 512, kFF = 1376, kHS = 176;
constexpr uint32_t SM_RING = 131072, SLOT = 24576, SM_MISC = 229376;
constexpr uint32_t SM_STAT = SM_MISC;
constexpr uint32_t SM_CS = SM_MISC + 1024;
constexpr uint32_t SM_BAR = SM_CS + 1472;
constexpr uint32_t B_BFULL = SM_BAR + 392  , B_BEMPTY = SM_BAR + 440  , B_AFULL = SM_BAR + 64  ,
                   B_AFREE = SM_BAR + 192  , B_OWN = SM_BAR + 240  , B_STAT = SM_BAR + 288  ,
                   B_CSRDY = SM_BAR + 304  , B_KVDONE = SM_BAR + 320, B_KVRDY = SM_BAR + 328,
                   B_PRDY = SM_BAR + 336  , B_PFREE = SM_BAR + 352  , B_CSQ = SM_BAR + 368, B_HPUB = SM_BAR + 376  ;
constexpr uint32_t B_EARLY = SM_BAR  , B_HP1 = SM_BAR + 16, B_HP2 = SM_BAR + 24;
constexpr uint32_t SM_TOTAL = SM_BAR + 488;
__host__ __device__ constexpr int st_slot(int st) { return st < 24 ? (st & 3) : (0x532410 >> (4 * (st < 30 ? st - 24 : st - 30))) & 7; }
__host__ __device__ constexpr int st_par(int st) { return st < 24 ? (st >> 2) & 1 : st >= 30; }
__host__ __device__ constexpr uint32_t st_off(int st) { return st < 24 ? (st & 3) * SLOT : (st < 30 ? st - 24 : st - 30) * 16384; }
static_assert(SM_TOTAL <= 232448, "smem");
constexpr uint32_t SPIN_LIMIT = 1u << 18;
constexpr int kSkew = 500;
constexpr int kKvDelay = 2000;
constexpr int kStraggler = 200;
constexpr int kStagger = 300;
constexpr int kHGate = 300, kHGate2 = 600;

struct Scratch {
  uint32_t epoch[128 * 8];
  uint4 flags[32 * 8 * 8 * 2];
  float4 cs[8 * 2 * 16 * 48];
  float4 kv[2 * 8 * 384];
  float2 stats[4 * 32 * 64 * 8];
  uint4 act[3 * 32 * 8 * 512];
  uint4 h[32 * 8 * 3 * 512];
};
__device__ __align__(1024) Scratch g_s;
#define g_epoch g_s.epoch
#define g_flags g_s.flags
#define g_cs g_s.cs
#define g_kv g_s.kv
#define g_stats g_s.stats
#define g_act g_s.act
#define g_h g_s.h

__device__ __forceinline__ uint32_t smem_u32(const void* p) { return (uint32_t)__cvta_generic_to_shared(p); }
__device__ __forceinline__ void mbar_init(uint32_t bar, uint32_t cnt) { asm volatile("mbarrier.init.shared::cta.b64 [%0], %1;" :: "r"(bar), "r"(cnt)); }
__device__ __forceinline__ void mbar_expect_tx(uint32_t bar, uint32_t bytes) { asm volatile("mbarrier.arrive.expect_tx.shared::cta.b64 _, [%0], %1;" :: "r"(bar), "r"(bytes) : "memory"); }
__device__ __forceinline__ void mbar_arrive(uint32_t bar) { asm volatile("mbarrier.arrive.shared::cta.b64 _, [%0];" :: "r"(bar) : "memory"); }
__device__ __forceinline__ void mbar_arrive_remote(uint32_t bar) { asm volatile("mbarrier.arrive.shared::cluster.b64 _, [%0];" :: "r"(bar) : "memory"); }
__device__ __forceinline__ void mbar_wait(uint32_t bar, uint32_t parity) {
  asm volatile("{\n.reg .pred p;\n.reg .u32 c;\nmov.u32 c, 0;\nWAIT_LOOP:\n"
               "mbarrier.try_wait.parity.shared::cta.b64 p, [%0], %1;\n@p bra WAIT_DONE;\n"
               "add.u32 c, c, 1;\nsetp.lt.u32 p, c, %2;\n@p bra WAIT_LOOP;\ntrap;\nWAIT_DONE:\n}"
               :: "r"(bar), "r"(parity), "n"(SPIN_LIMIT) : "memory");
}
__device__ __forceinline__ bool mbar_test(uint32_t bar, uint32_t parity) {
  uint32_t ok;
  asm volatile("{\n.reg .pred p;\nmbarrier.test_wait.parity.shared::cta.b64 p, [%1], %2;\nselp.u32 %0, 1, 0, p;\n}" : "=r"(ok) : "r"(bar), "r"(parity) : "memory");
  return ok;
}
__device__ __forceinline__ uint32_t mapa(uint32_t addr, uint32_t rank) { uint32_t r; asm volatile("mapa.shared::cluster.u32 %0, %1, %2;" : "=r"(r) : "r"(addr), "r"(rank)); return r; }
__device__ __forceinline__ bool elect_one() { uint32_t p; asm volatile("{\n.reg .pred P;\nelect.sync _|P, 0xffffffff;\nselp.u32 %0, 1, 0, P;\n}" : "=r"(p)); return p; }
__device__ __forceinline__ void bulk_g2s(uint32_t dst, const void* src, uint32_t bytes, uint32_t bar) {
  asm volatile("cp.async.bulk.shared::cluster.global.mbarrier::complete_tx::bytes [%0], [%1], %2, [%3];" :: "r"(dst), "l"(src), "r"(bytes), "r"(bar) : "memory");
}
__device__ __forceinline__ void bulk_s2g(void* dst, uint32_t src, uint32_t bytes) { asm volatile("cp.async.bulk.global.shared::cta.bulk_group [%0], [%1], %2;" :: "l"(dst), "r"(src), "r"(bytes) : "memory"); }
__device__ __forceinline__ void bulk_commit() { asm volatile("cp.async.bulk.commit_group;" ::: "memory"); }
template <int N> __device__ __forceinline__ void bulk_wait_read() { asm volatile("cp.async.bulk.wait_group.read %0;" :: "n"(N) : "memory"); }
template <int N> __device__ __forceinline__ void bulk_wait() { asm volatile("cp.async.bulk.wait_group %0;" :: "n"(N) : "memory"); }
__device__ __forceinline__ void tma_load(uint32_t dst, const CUtensorMap* m, int c0, int c1, uint32_t bar) {
  asm volatile("cp.async.bulk.tensor.2d.shared::cluster.global.mbarrier::complete_tx::bytes [%0], [%1, {%3, %4}], [%2];" :: "r"(dst), "l"(m), "r"(bar), "r"(c0), "r"(c1) : "memory");
}
__device__ __forceinline__ void tma_store(const CUtensorMap* m, uint32_t src, int c0, int c1) {
  asm volatile("cp.async.bulk.tensor.2d.global.shared::cta.bulk_group [%0, {%2, %3}], [%1];" :: "l"(m), "r"(src), "r"(c0), "r"(c1) : "memory");
}
__device__ __forceinline__ void prefetch_l2(const void* p, uint32_t bytes) { asm volatile("cp.async.bulk.prefetch.L2.global [%0], %1;" :: "l"(p), "r"(bytes) : "memory"); }
__device__ __forceinline__ void prefetch_map(const CUtensorMap* m) { asm volatile("prefetch.tensormap [%0];" :: "l"(m) : "memory"); }
__device__ __forceinline__ void fence_async_smem() { asm volatile("fence.proxy.async.shared::cta;" ::: "memory"); }
__device__ __forceinline__ void fence_gpu() { asm volatile("fence.acq_rel.gpu;" ::: "memory"); }
__device__ __forceinline__ uint32_t ld_relaxed(const uint32_t* p) { uint32_t v; asm volatile("ld.relaxed.gpu.global.u32 %0, [%1];" : "=r"(v) : "l"(p) : "memory"); return v; }
__device__ __forceinline__ float4 ld_relaxed_f4(const void* p) { float4 v; asm volatile("ld.relaxed.gpu.global.v4.f32 {%0,%1,%2,%3}, [%4];" : "=f"(v.x), "=f"(v.y), "=f"(v.z), "=f"(v.w) : "l"(p) : "memory"); return v; }
__device__ __forceinline__ void st_relaxed_b64(void* p, float a, uint32_t b) {
  asm volatile("{\n.reg .b64 v;\nmov.b64 v, {%1, %2};\nst.relaxed.gpu.global.b64 [%0], v;\n}" :: "l"(p), "r"(__float_as_uint(a)), "r"(b) : "memory");
}
__device__ __forceinline__ void red_add_f4(float* p, float a, float b, float c, float d) { asm volatile("red.relaxed.gpu.global.add.v4.f32 [%0], {%1, %2, %3, %4};" :: "l"(p), "f"(a), "f"(b), "f"(c), "f"(d) : "memory"); }
__device__ __forceinline__ void st_async_v4(uint32_t dst, uint32_t a, uint32_t b, uint32_t c, uint32_t d, uint32_t bar) {
  asm volatile("st.async.weak.shared::cluster.mbarrier::complete_tx::bytes.v4.b32 [%0], {%1,%2,%3,%4}, [%5];" :: "r"(dst), "r"(a), "r"(b), "r"(c), "r"(d), "r"(bar) : "memory");
}
__device__ __forceinline__ void stsm4(uint32_t addr, uint32_t a, uint32_t b, uint32_t c, uint32_t d) {
  asm volatile("stmatrix.sync.aligned.m8n8.x4.shared.b16 [%0], {%1,%2,%3,%4};" :: "r"(addr), "r"(a), "r"(b), "r"(c), "r"(d) : "memory");
}
__device__ __forceinline__ void ldsm4(uint32_t addr, uint32_t& a, uint32_t& b, uint32_t& c, uint32_t& d) {
  asm volatile("ldmatrix.sync.aligned.m8n8.x4.shared.b16 {%0,%1,%2,%3}, [%4];" : "=r"(a), "=r"(b), "=r"(c), "=r"(d) : "r"(addr) : "memory");
}
__device__ __forceinline__ void ldsm4t(uint32_t addr, uint32_t& a, uint32_t& b, uint32_t& c, uint32_t& d) {
  asm volatile("ldmatrix.sync.aligned.m8n8.x4.trans.shared.b16 {%0,%1,%2,%3}, [%4];" : "=r"(a), "=r"(b), "=r"(c), "=r"(d) : "r"(addr) : "memory");
}
__device__ __forceinline__ float2 lds_f2(uint32_t addr) { float2 v; asm volatile("ld.shared.v2.f32 {%0,%1}, [%2];" : "=f"(v.x), "=f"(v.y) : "r"(addr) : "memory"); return v; }
__device__ __forceinline__ uint32_t lds_u32(uint32_t addr) { uint32_t v; asm volatile("ld.shared.u32 %0, [%1];" : "=r"(v) : "r"(addr) : "memory"); return v; }
__device__ __forceinline__ void sts_u4(uint32_t addr, uint4 v) { asm volatile("st.shared.v4.u32 [%0], {%1,%2,%3,%4};" :: "r"(addr), "r"(v.x), "r"(v.y), "r"(v.z), "r"(v.w) : "memory"); }
__device__ __forceinline__ uint4 ld_relaxed_u4(const void* p) { uint4 v; asm volatile("ld.relaxed.gpu.global.v4.u32 {%0,%1,%2,%3}, [%4];" : "=r"(v.x), "=r"(v.y), "=r"(v.z), "=r"(v.w) : "l"(p) : "memory"); return v; }
__device__ __forceinline__ void st_relaxed_f4(void* p, float a, float b, float c, uint32_t d) { asm volatile("st.relaxed.gpu.global.v4.b32 [%0], {%1,%2,%3,%4};" :: "l"(p), "r"(__float_as_uint(a)), "r"(__float_as_uint(b)), "r"(__float_as_uint(c)), "r"(d) : "memory"); }
__device__ __forceinline__ uint2 lds_u2(uint32_t addr) { uint2 v; asm volatile("ld.shared.v2.u32 {%0,%1}, [%2];" : "=r"(v.x), "=r"(v.y) : "r"(addr) : "memory"); return v; }
__device__ __forceinline__ uint4 lds_u4(uint32_t addr) { uint4 v; asm volatile("ld.shared.v4.u32 {%0,%1,%2,%3}, [%4];" : "=r"(v.x), "=r"(v.y), "=r"(v.z), "=r"(v.w) : "r"(addr) : "memory"); return v; }
__device__ __forceinline__ void sts_u2(uint32_t addr, uint32_t a, uint32_t b) { asm volatile("st.shared.v2.u32 [%0], {%1,%2};" :: "r"(addr), "r"(a), "r"(b) : "memory"); }
__device__ __forceinline__ void sts_f4(uint32_t addr, float4 v) { asm volatile("st.shared.v4.f32 [%0], {%1,%2,%3,%4};" :: "r"(addr), "f"(v.x), "f"(v.y), "f"(v.z), "f"(v.w) : "memory"); }
__device__ __forceinline__ void mma16816(float (&c)[4], uint32_t a0, uint32_t a1, uint32_t a2, uint32_t a3, uint32_t b0, uint32_t b1) {
  asm volatile("mma.sync.aligned.m16n8k16.row.col.f32.bf16.bf16.f32 {%0,%1,%2,%3}, {%4,%5,%6,%7}, {%8,%9}, {%0,%1,%2,%3};"
               : "+f"(c[0]), "+f"(c[1]), "+f"(c[2]), "+f"(c[3]) : "r"(a0), "r"(a1), "r"(a2), "r"(a3), "r"(b0), "r"(b1));
}
__device__ __forceinline__ uint32_t pack_bf16(float lo, float hi) { uint32_t r; asm("cvt.rn.bf16x2.f32 %0, %1, %2;" : "=r"(r) : "f"(hi), "f"(lo)); return r; }
__device__ __forceinline__ uint32_t pack_bf16_relu(float lo, float hi) { uint32_t r; asm("cvt.rn.relu.bf16x2.f32 %0, %1, %2;" : "=r"(r) : "f"(hi), "f"(lo)); return r; }
__device__ __forceinline__ float bf_lo(uint32_t v) { return __uint_as_float(v << 16); }
__device__ __forceinline__ float bf_hi(uint32_t v) { return __uint_as_float(v & 0xffff0000u); }
__device__ __forceinline__ float ex2(float x) { float y; asm("ex2.approx.ftz.f32 %0, %1;" : "=f"(y) : "f"(x)); return y; }
__device__ __forceinline__ float rcp(float x) { float y; asm("rcp.approx.ftz.f32 %0, %1;" : "=f"(y) : "f"(x)); return y; }
__device__ __forceinline__ float phi_y(float y) { return fmaf(fmaxf(y, 1.4426950408889634e-6f), 0.6931471805599453f, ex2(fminf(y, 0.f))); }
__device__ __forceinline__ int opaque(int x) { int y; asm volatile("mov.u32 %0, %1;" : "=r"(y) : "r"(x)); return y; }
__device__ __forceinline__ void spin(int clks) { const uint32_t t0 = (uint32_t)clock(); while ((uint32_t)clock() - t0 < (uint32_t)clks) {} }
__device__ __forceinline__ void wg_fence() { asm volatile("wgmma.fence.sync.aligned;" ::: "memory"); }
__device__ __forceinline__ void wg_commit() { asm volatile("wgmma.commit_group.sync.aligned;" ::: "memory"); }
template <int N> __device__ __forceinline__ void wg_wait() { asm volatile("wgmma.wait_group.sync.aligned %0;" :: "n"(N) : "memory"); }
template <int N> __device__ __forceinline__ void fence_regs(float (&d)[N]) {
#pragma unroll
  for (int i = 0; i < N; i++) asm volatile("" : "+f"(d[i]) :: "memory");
}
template <int N> __device__ __forceinline__ void rename_regs(float (&d)[N], const float (&s)[N]) {
#pragma unroll
  for (int i = 0; i < N; i++) asm volatile("mov.f32 %0, %1;" : "=f"(d[i]) : "f"(s[i]));
}
__device__ __forceinline__ void wg_bar(int wg) { if (wg == 0) asm volatile("bar.sync 1, 128;" ::: "memory"); else asm volatile("bar.sync 2, 128;" ::: "memory"); }
__device__ __forceinline__ uint32_t desc_lo(uint32_t addr, uint32_t lbo) { return ((addr & 0x3FFFF) >> 4) | ((lbo >> 4) << 16); }
constexpr uint32_t HI_SW = 0x40000040u;
constexpr uint32_t HI_NS = 0x00000008u;
template <int I> struct IC { static constexpr int value = I; };
template <int B, int E, class F> __device__ __forceinline__ void static_for(F&& f) {
  if constexpr (B < E) { f(IC<B>{}); static_for<B + 1, E>(f); }
}

template <int OA, int OB, uint32_t HA>
__device__ __forceinline__ void wgmma_n64_init(float (&d)[32], uint32_t la, uint32_t lb) {
  asm volatile("{\n.reg .pred p;\n.reg .b32 ta, tb;\n.reg .b64 da, db;\n"
    "setp.ne.b32 p, 0, 0;\nadd.u32 ta, %32, %34;\nadd.u32 tb, %33, %35;\n"
    "mov.b64 da, {ta, %36};\nmov.b64 db, {tb, 0x40000040};\n"
    "wgmma.mma_async.sync.aligned.m64n64k16.f32.bf16.bf16 "
    "{%0, %1, %2, %3, %4, %5, %6, %7, %8, %9, %10, %11, %12, %13, %14, %15, "
    "%16, %17, %18, %19, %20, %21, %22, %23, %24, %25, %26, %27, %28, %29, %30, %31}, "
    "da, db, p, 1, 1, 0, 1;\n}"
    : "=f"(d[0]), "=f"(d[1]), "=f"(d[2]), "=f"(d[3]), "=f"(d[4]), "=f"(d[5]), "=f"(d[6]), "=f"(d[7]),
      "=f"(d[8]), "=f"(d[9]), "=f"(d[10]), "=f"(d[11]), "=f"(d[12]), "=f"(d[13]), "=f"(d[14]), "=f"(d[15]),
      "=f"(d[16]), "=f"(d[17]), "=f"(d[18]), "=f"(d[19]), "=f"(d[20]), "=f"(d[21]), "=f"(d[22]), "=f"(d[23]),
      "=f"(d[24]), "=f"(d[25]), "=f"(d[26]), "=f"(d[27]), "=f"(d[28]), "=f"(d[29]), "=f"(d[30]), "=f"(d[31])
    : "r"(la), "r"(lb), "n"(OA), "n"(OB), "n"(HA));
}
template <int OA, int OB, uint32_t HA>
__device__ __forceinline__ void wgmma_n128_init(float (&d)[32], float (&e)[32], uint32_t la, uint32_t lb) {
  asm volatile("{\n.reg .pred p;\n.reg .b32 ta, tb;\n.reg .b64 da, db;\n"
    "setp.ne.b32 p, 0, 0;\nadd.u32 ta, %64, %66;\nadd.u32 tb, %65, %67;\n"
    "mov.b64 da, {ta, %68};\nmov.b64 db, {tb, 0x40000040};\n"
    "wgmma.mma_async.sync.aligned.m64n128k16.f32.bf16.bf16 "
    "{%0, %1, %2, %3, %4, %5, %6, %7, %8, %9, %10, %11, %12, %13, %14, %15, "
    "%16, %17, %18, %19, %20, %21, %22, %23, %24, %25, %26, %27, %28, %29, %30, %31, "
    "%32, %33, %34, %35, %36, %37, %38, %39, %40, %41, %42, %43, %44, %45, %46, %47, "
    "%48, %49, %50, %51, %52, %53, %54, %55, %56, %57, %58, %59, %60, %61, %62, %63}, "
    "da, db, p, 1, 1, 0, 1;\n}"
    : "=f"(d[0]), "=f"(d[1]), "=f"(d[2]), "=f"(d[3]), "=f"(d[4]), "=f"(d[5]), "=f"(d[6]), "=f"(d[7]),
      "=f"(d[8]), "=f"(d[9]), "=f"(d[10]), "=f"(d[11]), "=f"(d[12]), "=f"(d[13]), "=f"(d[14]), "=f"(d[15]),
      "=f"(d[16]), "=f"(d[17]), "=f"(d[18]), "=f"(d[19]), "=f"(d[20]), "=f"(d[21]), "=f"(d[22]), "=f"(d[23]),
      "=f"(d[24]), "=f"(d[25]), "=f"(d[26]), "=f"(d[27]), "=f"(d[28]), "=f"(d[29]), "=f"(d[30]), "=f"(d[31]),
      "=f"(e[0]), "=f"(e[1]), "=f"(e[2]), "=f"(e[3]), "=f"(e[4]), "=f"(e[5]), "=f"(e[6]), "=f"(e[7]),
      "=f"(e[8]), "=f"(e[9]), "=f"(e[10]), "=f"(e[11]), "=f"(e[12]), "=f"(e[13]), "=f"(e[14]), "=f"(e[15]),
      "=f"(e[16]), "=f"(e[17]), "=f"(e[18]), "=f"(e[19]), "=f"(e[20]), "=f"(e[21]), "=f"(e[22]), "=f"(e[23]),
      "=f"(e[24]), "=f"(e[25]), "=f"(e[26]), "=f"(e[27]), "=f"(e[28]), "=f"(e[29]), "=f"(e[30]), "=f"(e[31])
    : "r"(la), "r"(lb), "n"(OA), "n"(OB), "n"(HA));
}
template <int OA, int OB, uint32_t HA>
__device__ __forceinline__ void wgmma_n176_init(float (&d)[32], float (&e)[56], uint32_t la, uint32_t lb) {
  asm volatile("{\n.reg .pred p;\n.reg .b32 ta, tb;\n.reg .b64 da, db;\n"
    "setp.ne.b32 p, 0, 0;\nadd.u32 ta, %88, %90;\nadd.u32 tb, %89, %91;\n"
    "mov.b64 da, {ta, %92};\nmov.b64 db, {tb, 0x40000040};\n"
    "wgmma.mma_async.sync.aligned.m64n176k16.f32.bf16.bf16 "
    "{%0, %1, %2, %3, %4, %5, %6, %7, %8, %9, %10, %11, %12, %13, %14, %15, "
    "%16, %17, %18, %19, %20, %21, %22, %23, %24, %25, %26, %27, %28, %29, %30, %31, "
    "%32, %33, %34, %35, %36, %37, %38, %39, %40, %41, %42, %43, %44, %45, %46, %47, "
    "%48, %49, %50, %51, %52, %53, %54, %55, %56, %57, %58, %59, %60, %61, %62, %63, "
    "%64, %65, %66, %67, %68, %69, %70, %71, %72, %73, %74, %75, %76, %77, %78, %79, "
    "%80, %81, %82, %83, %84, %85, %86, %87}, "
    "da, db, p, 1, 1, 0, 1;\n}"
    : "=f"(d[0]), "=f"(d[1]), "=f"(d[2]), "=f"(d[3]), "=f"(d[4]), "=f"(d[5]), "=f"(d[6]), "=f"(d[7]),
      "=f"(d[8]), "=f"(d[9]), "=f"(d[10]), "=f"(d[11]), "=f"(d[12]), "=f"(d[13]), "=f"(d[14]), "=f"(d[15]),
      "=f"(d[16]), "=f"(d[17]), "=f"(d[18]), "=f"(d[19]), "=f"(d[20]), "=f"(d[21]), "=f"(d[22]), "=f"(d[23]),
      "=f"(d[24]), "=f"(d[25]), "=f"(d[26]), "=f"(d[27]), "=f"(d[28]), "=f"(d[29]), "=f"(d[30]), "=f"(d[31]),
      "=f"(e[0]), "=f"(e[1]), "=f"(e[2]), "=f"(e[3]), "=f"(e[4]), "=f"(e[5]), "=f"(e[6]), "=f"(e[7]),
      "=f"(e[8]), "=f"(e[9]), "=f"(e[10]), "=f"(e[11]), "=f"(e[12]), "=f"(e[13]), "=f"(e[14]), "=f"(e[15]),
      "=f"(e[16]), "=f"(e[17]), "=f"(e[18]), "=f"(e[19]), "=f"(e[20]), "=f"(e[21]), "=f"(e[22]), "=f"(e[23]),
      "=f"(e[24]), "=f"(e[25]), "=f"(e[26]), "=f"(e[27]), "=f"(e[28]), "=f"(e[29]), "=f"(e[30]), "=f"(e[31]),
      "=f"(e[32]), "=f"(e[33]), "=f"(e[34]), "=f"(e[35]), "=f"(e[36]), "=f"(e[37]), "=f"(e[38]), "=f"(e[39]),
      "=f"(e[40]), "=f"(e[41]), "=f"(e[42]), "=f"(e[43]), "=f"(e[44]), "=f"(e[45]), "=f"(e[46]), "=f"(e[47]),
      "=f"(e[48]), "=f"(e[49]), "=f"(e[50]), "=f"(e[51]), "=f"(e[52]), "=f"(e[53]), "=f"(e[54]), "=f"(e[55])
    : "r"(la), "r"(lb), "n"(OA), "n"(OB), "n"(HA));
}
template <int OA, int OB, uint32_t HA>
__device__ __forceinline__ void wgmma_n64(float (&d)[32], uint32_t la, uint32_t lb) {
  asm volatile("{\n.reg .pred p;\n.reg .b32 ta, tb;\n.reg .b64 da, db;\n"
    "setp.eq.b32 p, 0, 0;\nadd.u32 ta, %32, %34;\nadd.u32 tb, %33, %35;\n"
    "mov.b64 da, {ta, %36};\nmov.b64 db, {tb, 0x40000040};\n"
    "wgmma.mma_async.sync.aligned.m64n64k16.f32.bf16.bf16 "
    "{%0, %1, %2, %3, %4, %5, %6, %7, %8, %9, %10, %11, %12, %13, %14, %15, "
    "%16, %17, %18, %19, %20, %21, %22, %23, %24, %25, %26, %27, %28, %29, %30, %31}, "
    "da, db, p, 1, 1, 0, 1;\n}"
    : "+f"(d[0]), "+f"(d[1]), "+f"(d[2]), "+f"(d[3]), "+f"(d[4]), "+f"(d[5]), "+f"(d[6]), "+f"(d[7]),
      "+f"(d[8]), "+f"(d[9]), "+f"(d[10]), "+f"(d[11]), "+f"(d[12]), "+f"(d[13]), "+f"(d[14]), "+f"(d[15]),
      "+f"(d[16]), "+f"(d[17]), "+f"(d[18]), "+f"(d[19]), "+f"(d[20]), "+f"(d[21]), "+f"(d[22]), "+f"(d[23]),
      "+f"(d[24]), "+f"(d[25]), "+f"(d[26]), "+f"(d[27]), "+f"(d[28]), "+f"(d[29]), "+f"(d[30]), "+f"(d[31])
    : "r"(la), "r"(lb), "n"(OA), "n"(OB), "n"(HA));
}
template <int OA, int OB, uint32_t HA>
__device__ __forceinline__ void wgmma_n128(float (&d)[32], float (&e)[32], uint32_t la, uint32_t lb) {
  asm volatile("{\n.reg .pred p;\n.reg .b32 ta, tb;\n.reg .b64 da, db;\n"
    "setp.eq.b32 p, 0, 0;\nadd.u32 ta, %64, %66;\nadd.u32 tb, %65, %67;\n"
    "mov.b64 da, {ta, %68};\nmov.b64 db, {tb, 0x40000040};\n"
    "wgmma.mma_async.sync.aligned.m64n128k16.f32.bf16.bf16 "
    "{%0, %1, %2, %3, %4, %5, %6, %7, %8, %9, %10, %11, %12, %13, %14, %15, "
    "%16, %17, %18, %19, %20, %21, %22, %23, %24, %25, %26, %27, %28, %29, %30, %31, "
    "%32, %33, %34, %35, %36, %37, %38, %39, %40, %41, %42, %43, %44, %45, %46, %47, "
    "%48, %49, %50, %51, %52, %53, %54, %55, %56, %57, %58, %59, %60, %61, %62, %63}, "
    "da, db, p, 1, 1, 0, 1;\n}"
    : "+f"(d[0]), "+f"(d[1]), "+f"(d[2]), "+f"(d[3]), "+f"(d[4]), "+f"(d[5]), "+f"(d[6]), "+f"(d[7]),
      "+f"(d[8]), "+f"(d[9]), "+f"(d[10]), "+f"(d[11]), "+f"(d[12]), "+f"(d[13]), "+f"(d[14]), "+f"(d[15]),
      "+f"(d[16]), "+f"(d[17]), "+f"(d[18]), "+f"(d[19]), "+f"(d[20]), "+f"(d[21]), "+f"(d[22]), "+f"(d[23]),
      "+f"(d[24]), "+f"(d[25]), "+f"(d[26]), "+f"(d[27]), "+f"(d[28]), "+f"(d[29]), "+f"(d[30]), "+f"(d[31]),
      "+f"(e[0]), "+f"(e[1]), "+f"(e[2]), "+f"(e[3]), "+f"(e[4]), "+f"(e[5]), "+f"(e[6]), "+f"(e[7]),
      "+f"(e[8]), "+f"(e[9]), "+f"(e[10]), "+f"(e[11]), "+f"(e[12]), "+f"(e[13]), "+f"(e[14]), "+f"(e[15]),
      "+f"(e[16]), "+f"(e[17]), "+f"(e[18]), "+f"(e[19]), "+f"(e[20]), "+f"(e[21]), "+f"(e[22]), "+f"(e[23]),
      "+f"(e[24]), "+f"(e[25]), "+f"(e[26]), "+f"(e[27]), "+f"(e[28]), "+f"(e[29]), "+f"(e[30]), "+f"(e[31])
    : "r"(la), "r"(lb), "n"(OA), "n"(OB), "n"(HA));
}
template <int OA, int OB, uint32_t HA>
__device__ __forceinline__ void wgmma_n176(float (&d)[32], float (&e)[56], uint32_t la, uint32_t lb) {
  asm volatile("{\n.reg .pred p;\n.reg .b32 ta, tb;\n.reg .b64 da, db;\n"
    "setp.eq.b32 p, 0, 0;\nadd.u32 ta, %88, %90;\nadd.u32 tb, %89, %91;\n"
    "mov.b64 da, {ta, %92};\nmov.b64 db, {tb, 0x40000040};\n"
    "wgmma.mma_async.sync.aligned.m64n176k16.f32.bf16.bf16 "
    "{%0, %1, %2, %3, %4, %5, %6, %7, %8, %9, %10, %11, %12, %13, %14, %15, "
    "%16, %17, %18, %19, %20, %21, %22, %23, %24, %25, %26, %27, %28, %29, %30, %31, "
    "%32, %33, %34, %35, %36, %37, %38, %39, %40, %41, %42, %43, %44, %45, %46, %47, "
    "%48, %49, %50, %51, %52, %53, %54, %55, %56, %57, %58, %59, %60, %61, %62, %63, "
    "%64, %65, %66, %67, %68, %69, %70, %71, %72, %73, %74, %75, %76, %77, %78, %79, "
    "%80, %81, %82, %83, %84, %85, %86, %87}, "
    "da, db, p, 1, 1, 0, 1;\n}"
    : "+f"(d[0]), "+f"(d[1]), "+f"(d[2]), "+f"(d[3]), "+f"(d[4]), "+f"(d[5]), "+f"(d[6]), "+f"(d[7]),
      "+f"(d[8]), "+f"(d[9]), "+f"(d[10]), "+f"(d[11]), "+f"(d[12]), "+f"(d[13]), "+f"(d[14]), "+f"(d[15]),
      "+f"(d[16]), "+f"(d[17]), "+f"(d[18]), "+f"(d[19]), "+f"(d[20]), "+f"(d[21]), "+f"(d[22]), "+f"(d[23]),
      "+f"(d[24]), "+f"(d[25]), "+f"(d[26]), "+f"(d[27]), "+f"(d[28]), "+f"(d[29]), "+f"(d[30]), "+f"(d[31]),
      "+f"(e[0]), "+f"(e[1]), "+f"(e[2]), "+f"(e[3]), "+f"(e[4]), "+f"(e[5]), "+f"(e[6]), "+f"(e[7]),
      "+f"(e[8]), "+f"(e[9]), "+f"(e[10]), "+f"(e[11]), "+f"(e[12]), "+f"(e[13]), "+f"(e[14]), "+f"(e[15]),
      "+f"(e[16]), "+f"(e[17]), "+f"(e[18]), "+f"(e[19]), "+f"(e[20]), "+f"(e[21]), "+f"(e[22]), "+f"(e[23]),
      "+f"(e[24]), "+f"(e[25]), "+f"(e[26]), "+f"(e[27]), "+f"(e[28]), "+f"(e[29]), "+f"(e[30]), "+f"(e[31]),
      "+f"(e[32]), "+f"(e[33]), "+f"(e[34]), "+f"(e[35]), "+f"(e[36]), "+f"(e[37]), "+f"(e[38]), "+f"(e[39]),
      "+f"(e[40]), "+f"(e[41]), "+f"(e[42]), "+f"(e[43]), "+f"(e[44]), "+f"(e[45]), "+f"(e[46]), "+f"(e[47]),
      "+f"(e[48]), "+f"(e[49]), "+f"(e[50]), "+f"(e[51]), "+f"(e[52]), "+f"(e[53]), "+f"(e[54]), "+f"(e[55])
    : "r"(la), "r"(lb), "n"(OA), "n"(OB), "n"(HA));
}
template <int OA, int OB, uint32_t HA>
__device__ __forceinline__ void wgmma_n112(float (&d)[56], uint32_t la, uint32_t lb) {
  asm volatile("{\n.reg .pred p;\n.reg .b32 ta, tb;\n.reg .b64 da, db;\n"
    "setp.eq.b32 p, 0, 0;\nadd.u32 ta, %56, %58;\nadd.u32 tb, %57, %59;\n"
    "mov.b64 da, {ta, %60};\nmov.b64 db, {tb, 0x40000040};\n"
    "wgmma.mma_async.sync.aligned.m64n112k16.f32.bf16.bf16 "
    "{%0, %1, %2, %3, %4, %5, %6, %7, %8, %9, %10, %11, %12, %13, %14, %15, "
    "%16, %17, %18, %19, %20, %21, %22, %23, %24, %25, %26, %27, %28, %29, %30, %31, "
    "%32, %33, %34, %35, %36, %37, %38, %39, %40, %41, %42, %43, %44, %45, %46, %47, "
    "%48, %49, %50, %51, %52, %53, %54, %55}, "
    "da, db, p, 1, 1, 0, 1;\n}"
    : "+f"(d[0]), "+f"(d[1]), "+f"(d[2]), "+f"(d[3]), "+f"(d[4]), "+f"(d[5]), "+f"(d[6]), "+f"(d[7]),
      "+f"(d[8]), "+f"(d[9]), "+f"(d[10]), "+f"(d[11]), "+f"(d[12]), "+f"(d[13]), "+f"(d[14]), "+f"(d[15]),
      "+f"(d[16]), "+f"(d[17]), "+f"(d[18]), "+f"(d[19]), "+f"(d[20]), "+f"(d[21]), "+f"(d[22]), "+f"(d[23]),
      "+f"(d[24]), "+f"(d[25]), "+f"(d[26]), "+f"(d[27]), "+f"(d[28]), "+f"(d[29]), "+f"(d[30]), "+f"(d[31]),
      "+f"(d[32]), "+f"(d[33]), "+f"(d[34]), "+f"(d[35]), "+f"(d[36]), "+f"(d[37]), "+f"(d[38]), "+f"(d[39]),
      "+f"(d[40]), "+f"(d[41]), "+f"(d[42]), "+f"(d[43]), "+f"(d[44]), "+f"(d[45]), "+f"(d[46]), "+f"(d[47]),
      "+f"(d[48]), "+f"(d[49]), "+f"(d[50]), "+f"(d[51]), "+f"(d[52]), "+f"(d[53]), "+f"(d[54]), "+f"(d[55])
    : "r"(la), "r"(lb), "n"(OA), "n"(OB), "n"(HA));
}


__device__ __forceinline__ void publish_stats(const uint32_t (&xr)[16], float2* dst  , int t, uint32_t tag) {
  float s0 = 0.f, s1 = 0.f;
#pragma unroll
  for (int j = 0; j < 8; j++) { s0 += bf_lo(xr[2 * j]) + bf_hi(xr[2 * j]); s1 += bf_lo(xr[2 * j + 1]) + bf_hi(xr[2 * j + 1]); }
  s0 += __shfl_xor_sync(0xffffffff, s0, 1); s1 += __shfl_xor_sync(0xffffffff, s1, 1);
  s0 += __shfl_xor_sync(0xffffffff, s0, 2); s1 += __shfl_xor_sync(0xffffffff, s1, 2);
  const float m0 = s0 * (1.f / 64.f), m1 = s1 * (1.f / 64.f);
  float q0 = 0.f, q1 = 0.f;
#pragma unroll
  for (int j = 0; j < 8; j++) {
    float a = bf_lo(xr[2 * j]) - m0, b = bf_hi(xr[2 * j]) - m0, c = bf_lo(xr[2 * j + 1]) - m1, d = bf_hi(xr[2 * j + 1]) - m1;
    q0 = fmaf(a, a, q0); q0 = fmaf(b, b, q0); q1 = fmaf(c, c, q1); q1 = fmaf(d, d, q1);
  }
  q0 += __shfl_xor_sync(0xffffffff, q0, 1); q1 += __shfl_xor_sync(0xffffffff, q1, 1);
  q0 += __shfl_xor_sync(0xffffffff, q0, 2); q1 += __shfl_xor_sync(0xffffffff, q1, 2);
  if (t < 2) st_relaxed_b64(dst + 8 * t, t ? s1 : s0, (__float_as_uint(t ? q1 : q0) & ~1u) | tag);
}

__device__ __forceinline__ void gather_stats(const float2* src  , uint32_t sm_dst, uint32_t bar, int lane, uint32_t tag) {
  const float2* p = src + lane * 2;
  float4 v[8];
  uint32_t cnt = 0;
  while (true) {
#pragma unroll
    for (int i = 0; i < 8; i++) v[i] = ld_relaxed_f4(p + i * 64);
    uint32_t bad = 0;
#pragma unroll
    for (int i = 0; i < 8; i++) bad |= (__float_as_uint(v[i].y) ^ tag) | (__float_as_uint(v[i].w) ^ tag);
    if (__all_sync(0xffffffff, (bad & 1u) == 0)) break;
    if (++cnt > SPIN_LIMIT) __trap();
    __nanosleep(100);
  }
  float sa = 0.f, sb = 0.f, qa = 0.f, qb = 0.f;
#pragma unroll
  for (int i = 0; i < 8; i++) { sa += v[i].x; qa += v[i].y; sb += v[i].z; qb += v[i].w; }
  const float ma = sa * (1.f / 512.f), mb = sb * (1.f / 512.f);
  float da = 0.f, db = 0.f;
#pragma unroll
  for (int i = 0; i < 8; i++) {
    const float a = v[i].x * (1.f / 64.f) - ma, b = v[i].z * (1.f / 64.f) - mb;
    da = fmaf(a, a, da); db = fmaf(b, b, db);
  }
  sts_f4(sm_dst + lane * 16, make_float4(rsqrtf(fmaf(da, 64.f, qa) * (1.f / 512.f) + 1e-5f), -ma, rsqrtf(fmaf(db, 64.f, qb) * (1.f / 512.f) + 1e-5f), -mb));
  __syncwarp();
  if (lane == 0) mbar_arrive(bar);
}

__device__ __forceinline__ void colsum_load(uint4 (&v)[8], const __nv_bfloat16* p  , int pitch, bool ok, int row0, int lane) {
#pragma unroll
  for (int i = 0; i < 8; i++) {
    v[i] = make_uint4(0, 0, 0, 0);
    if (ok) asm volatile("ld.global.nc.v4.u32 {%0,%1,%2,%3}, [%4];" : "=r"(v[i].x), "=r"(v[i].y), "=r"(v[i].z), "=r"(v[i].w) : "l"(p + (size_t)(row0 + 4 * i + (lane >> 3)) * pitch));
  }
}
__device__ __forceinline__ void colsum_publish(const uint4 (&v)[8], float4* dst  , int lane, uint32_t tag) {
  float a[8];
#pragma unroll
  for (int i = 0; i < 8; i++) a[i] = 0.f;
#pragma unroll
  for (int i = 0; i < 8; i++) {
    a[0] += bf_lo(v[i].x); a[1] += bf_hi(v[i].x); a[2] += bf_lo(v[i].y); a[3] += bf_hi(v[i].y);
    a[4] += bf_lo(v[i].z); a[5] += bf_hi(v[i].z); a[6] += bf_lo(v[i].w); a[7] += bf_hi(v[i].w);
  }
#pragma unroll
  for (int i = 0; i < 8; i++) { a[i] += __shfl_xor_sync(0xffffffff, a[i], 8); a[i] += __shfl_xor_sync(0xffffffff, a[i], 16); }
  if (lane < 8) {
    st_relaxed_f4(dst, a[0], a[1], a[2], (__float_as_uint(a[3]) & ~1u) | tag);
    st_relaxed_f4(dst + 1, a[4], a[5], a[6], (__float_as_uint(a[7]) & ~1u) | tag);
  }
}
__device__ __forceinline__ void colsum_gather(const float4* src, uint32_t sm_dst, int j0, int j1, int nunits, int lane, uint32_t tag) {
#pragma unroll 1
  for (int j = j0; j < j1; j++) {
    const float4* p = src + (lane >> 4) * 8 * 48 + j * 16 + (lane & 15);
    float4 v[8];
    uint32_t cnt = 0;
    while (true) {
      uint32_t bad = 0;
#pragma unroll
      for (int i = 0; i < 8; i++) v[i] = ld_relaxed_f4(p + i * 48);
#pragma unroll
      for (int i = 0; i < 8; i++) bad |= __float_as_uint(v[i].w) ^ tag;
      if (__all_sync(0xffffffff, (bad & 1u) == 0)) break;
      if (++cnt > SPIN_LIMIT) __trap();
      __nanosleep(100);
    }
    float4 a = v[0];
#pragma unroll
    for (int i = 1; i < 8; i++) { a.x += v[i].x; a.y += v[i].y; a.z += v[i].z; a.w += v[i].w; }
    a.x += __shfl_xor_sync(0xffffffff, a.x, 16); a.y += __shfl_xor_sync(0xffffffff, a.y, 16);
    a.z += __shfl_xor_sync(0xffffffff, a.z, 16); a.w += __shfl_xor_sync(0xffffffff, a.w, 16);
    if (lane < 16 && j * 16 + lane < nunits) sts_f4(sm_dst + (j * 16 + lane) * 16, a);
  }
  __syncwarp();
}

__device__ __forceinline__ void set_flags(uint4* flag  , uint32_t ev, int lane) {
  if (lane < 16) asm volatile("st.relaxed.gpu.global.v4.u32 [%0], {%1,%1,%1,%1};" :: "l"(flag + (lane >> 1) * 16 + (lane & 1)), "r"(ev) : "memory");
}
__device__ __forceinline__ void publish_chunk(uint4* gdst, uint32_t src, uint4* flag, uint32_t ev, int lane) {
  if (lane == 0) { bulk_s2g(gdst, src, 8192); bulk_commit(); }
  __syncwarp();
  set_flags(flag, ev, lane);
  if (lane == 0) bulk_wait_read<0>();
  __syncwarp();
}
template <int N, int STR>
__device__ __forceinline__ void fetch_chunks(const uint4* gbuf  , const uint4* flags, uint32_t abase, uint32_t afull, int r, uint32_t ev, int lane) {
  const uint32_t* f = (const uint32_t*)(flags + r * 16 + ((r ^ (STR * lane)) & 7) * 2);
  uint32_t todo = (1u << N) - 2, cnt = 0;
  if (lane >= 1 && lane < N) mbar_expect_tx(afull + lane * 8, 8192);
  while (todo) {
    uint32_t rdy;
    if (todo != (1u << N) - 2) { spin(kStraggler); rdy = todo; }
    else rdy = __ballot_sync(0xffffffff, (int32_t)(ld_relaxed(f) - ev) >= 0) & todo;
#pragma unroll
    for (int i = 1; i < N; i++) {
      if ((rdy >> i) & 1) {
        if (elect_one()) bulk_g2s(abase + i * 8192, gbuf + (r ^ (STR * i)) * 512, 8192, afull + i * 8);
        if (N == 8 && i == 1) spin(kStagger);
      }
    }
    todo &= ~rdy;
    if (++cnt > SPIN_LIMIT) __trap();
  }
  __syncwarp();
}

__device__ __forceinline__ int first_chunk(int i, int r) { return i == 0 ? r : i - 1 + (i - 1 >= r); }

__global__ void __cluster_dims__(2, 1, 1) __launch_bounds__(384, 1)
fused_kernel(const __grid_constant__ CUtensorMap tm_x, const __grid_constant__ CUtensorMap tm_out,
             const __grid_constant__ CUtensorMap tm_wqkv, const __grid_constant__ CUtensorMap tm_wo,
             const __grid_constant__ CUtensorMap tm_w1, const __grid_constant__ CUtensorMap tm_w2, const __grid_constant__ CUtensorMap tm_w2s,
             const __nv_bfloat16* __restrict__ wqkv, const __nv_bfloat16* __restrict__ wo,
             const __nv_bfloat16* __restrict__ w1, const __nv_bfloat16* __restrict__ w2) {
  extern __shared__ __align__(1024) uint8_t smem_raw[];
  const uint32_t sb = smem_u32(smem_raw);
  const int warp = __shfl_sync(0xffffffff, threadIdx.x >> 5, 0);
  const int bid = __shfl_sync(0xffffffff, opaque(blockIdx.x), 0);
  int cb, r;
  {
    const int cl = bid >> 1;
    int m;
    if (cl < 4) { cb = 15; m = cl; } else if (cl < 36) { cb = (cl - 4) & 7; m = (cl - 4) >> 3; } else { cb = 8 + (cl - 36) % 7; m = (cl - 36) / 7; }
    r = m * 2 + (bid & 1);
  }

  if (threadIdx.x == 0) {
    if (sb & 1023) __trap();
    for (int i = 0; i < 6; i++) { mbar_init(sb + B_BFULL + i * 8, 1); mbar_init(sb + B_BEMPTY + i * 8, 8); }
    for (int i = 0; i < 16; i++) mbar_init(sb + B_AFULL + i * 8, 1);
    for (int i = 0; i < 6; i++) { mbar_init(sb + B_AFREE + i * 8, i % 3 == 1 ? 5 : 4); mbar_init(sb + B_OWN + i * 8, i % 3 == 2 ? 1 : 4); }
    for (int i = 0; i < 2; i++) { mbar_init(sb + B_STAT + i * 8, 1); mbar_init(sb + B_PRDY + i * 8, 1); mbar_init(sb + B_PFREE + i * 8, 4); mbar_init(sb + B_HPUB + i * 8, 1); mbar_init(sb + B_EARLY + i * 8, 4); }
    mbar_init(sb + B_CSRDY, 2); mbar_init(sb + B_CSRDY + 8, 1); mbar_init(sb + B_CSQ, 1); mbar_init(sb + B_HP1, 1); mbar_init(sb + B_HP2, 1); mbar_init(sb + B_KVDONE, 4); mbar_init(sb + B_KVRDY, 1);
    asm volatile("fence.mbarrier_init.release.cluster;" ::: "memory");
  }
  __syncthreads();
  asm volatile("barrier.cluster.arrive.relaxed.aligned;" ::: "memory");

  if (warp >= 8) {
  asm volatile("setmaxnreg.dec.sync.aligned.u32 88;");
  const int lane = __shfl_sync(0xffffffff, threadIdx.x & 31, threadIdx.x & 31);
  const uint32_t epoch = ld_relaxed(g_epoch + bid * 8);
  if (warp == 8) {
    if (lane == 0) { prefetch_map(&tm_wqkv); prefetch_map(&tm_wo); prefetch_map(&tm_w1); prefetch_map(&tm_w2); prefetch_map(&tm_w2s); }
    auto released = [&](int st) { mbar_wait(sb + B_BEMPTY + st_slot(st) * 8, st_par(st)); };
#pragma unroll 1
    for (int l = 0; l < 2; l++) {
#pragma unroll 1
      for (int st = 0; st < 36; st++) {
        if (st < 4) { if (l > 0) { released(30 + st + (st >> 1)); if (st & 1) released(31 + st + (st >> 1)); } }
        else if (st < 24) released(st - 4);
        else if (st < 30) { if (st != 26 && st != 29) released(st < 26 ? st - 4 : st - 5); }
        else released(st - 6);
        const uint32_t dst = sb + SM_RING + st_off(st), fb = sb + B_BFULL + st_slot(st) * 8;
        const CUtensorMap* m;
        int c0, c1, r0, r1;
        uint32_t bytes = 16384;
        if (st < 8) { m = &tm_wqkv; c0 = 512 + 64 * r; c1 = c0 + 512; r0 = r1 = 64 * (l == 0 ? first_chunk(st, r) : r ^ st); }
        else if (st < 12) { m = &tm_wqkv; c0 = c1 = 64 * r; r0 = 64 * (r ^ (2 * st - 16)); r1 = r0 ^ 64; }
        else if (st < 16) { m = &tm_wo; c0 = 64 * (r ^ 1); c1 = 64 * r; r0 = r1 = 64 * (r ^ (2 * st - 24)); }
        else if (st < 24) { m = &tm_w1; c0 = kHS * r; c1 = c0 + 64; r0 = r1 = 64 * (r ^ (st - 16)); bytes = 24576; }
        else {
          const int i = st - 24, bb = i < 3 ? i : i / 3 - 1, t = i < 3 ? 0 : i - 3 * bb - 2;
          m = bb == 2 ? &tm_w2s : &tm_w2; c0 = 64 * (r ^ 1); c1 = 64 * r; r0 = r1 = kHS * (r ^ (2 * t)) + 64 * bb;
          if (bb == 2) bytes = 12288;
        }
        if (elect_one()) {
          mbar_expect_tx(fb, bytes); tma_load(dst, m, c0, r0, fb); tma_load(dst + 8192, m, c1, r1, fb);
          if (bytes == 24576) tma_load(dst + 16384, m, c1 + 64, r1, fb);
        }
      }
    }
    asm volatile("barrier.cluster.wait.aligned;" ::: "memory");
  } else if (warp == 9 || warp == 10) {
    const int h = warp - 9, half0 = cb * 2 + h;
    if (elect_one()) {
      const uint32_t abase = sb + h * 65536, afull = sb + B_AFULL + h * 64;
      prefetch_map(&tm_x);
      for (int i = 0; i < 8; i++) {
        const int j = first_chunk(i, r), slot = j ^ r;
        mbar_expect_tx(afull + slot * 8, 8192); tma_load(abase + slot * 8192, &tm_x, 64 * j, 128 * cb + 64 * h, afull + slot * 8);
      }
    }
    __syncwarp();
    const uint32_t ev0 = epoch * 16, tag = (epoch + 1) & 1;
    set_flags(g_flags + half0 * 128 + r * 2, ev0, lane);
    uint4 cv[8];
    mbar_wait(sb + B_AFULL + h * 64 + (first_chunk(1, r) ^ r) * 8, 0);
    colsum_gather(g_cs + (r * 2 + 0) * 16 * 48, sb + SM_CS, 1 + h, 2 + h, 48, lane, tag);
    if (lane == 0) mbar_arrive(sb + B_CSRDY);
    gather_stats(g_stats + (0 * 32 + half0) * 512, sb + SM_STAT + h * 512, sb + B_STAT + h * 8, lane, tag);
#pragma unroll 1
    for (int b = h; b < 3; b += 2) {
      const int col = 64 * b + 8 * (lane & 7);
      colsum_load(cv, w1 + kHS * r + col, kFF, col < kHS && kHS * r + col < kFF, 32 * cb, lane);
      colsum_publish(cv, g_cs + ((r * 2 + 1) * 16 + cb) * 48 + b * 16 + 2 * (lane & 7), lane, tag);
    }
    asm volatile("barrier.cluster.wait.aligned;" ::: "memory");
    uint32_t p0 = 0, po = 0;
#pragma unroll 1
    for (int l = 0; l < 2; l++) {
      const uint32_t ev = ev0 + l * 6;
      const int half = opaque(half0);
      const uint32_t abase = sb + h * 65536, afull = sb + B_AFULL + h * 64, afree = sb + B_AFREE + h * 24, own = sb + B_OWN + h * 24;
      uint4* flags = g_flags + half * 128;
      mbar_wait(own + 16, po); po ^= 1;
      mbar_wait(afree, p0); p0 ^= 1;
      fetch_chunks<4, 2>(g_act + (0 * 32 + half) * 4096, flags, abase, afull, r, ev + 1, lane);
      mbar_wait(own + 16, po); po ^= 1;
      mbar_wait(afree, p0); p0 ^= 1;
      fetch_chunks<8, 1>(g_act + (1 * 32 + half) * 4096, flags, abase, afull, r, ev + 2, lane);
      gather_stats(g_stats + ((2 * l + 1) * 32 + half) * 512, sb + SM_STAT + h * 512, sb + B_STAT + h * 8, lane, tag);
      {
        uint4* hb = g_h + half * 8 * 1536;
        mbar_wait(own, l);
        publish_chunk(hb + r * 1536, abase, flags + r * 2, ev + 3, lane);
        if (lane == 0) mbar_arrive(sb + B_HPUB + h * 8);
        const uint32_t* f = (const uint32_t*)(flags + r * 16 + (r ^ (2 + 2 * (lane % 3))) * 2);
        uint32_t todo = 0x1ff, cnt = 0, t1 = 0, t2 = 0;
        mbar_wait(sb + B_EARLY + h * 8, l);
        while (todo) {
          uint32_t fv = ev + 2;
          if (todo & 7) fv = ld_relaxed(f);
          uint32_t go = 0;
          if (!t1 && mbar_test(sb + B_HP1, l)) { mbar_wait(afree, p0); t1 = (uint32_t)clock() | 1; }
          if (!t2 && mbar_test(sb + B_HP2, l)) t2 = (uint32_t)clock() | 1;
          if (t1 && (uint32_t)clock() - t1 > kHGate) {
            const bool g5 = mbar_test(afree + 8, l), g6 = t2 && (uint32_t)clock() - t2 > kHGate2, g8 = mbar_test(afree + 16, l);
            go = 0x18 | (g5 ? 0x20 : 0) | (g5 && g6 ? 0xc0 : 0) | (g6 && g8 ? 0x100 : 0);
          }
          go = __shfl_sync(0xffffffff, go, 0);
#pragma unroll 1
          for (int pass = 0; pass < 2; pass++) {
            uint32_t m = (pass == 0 ? go : __ballot_sync(0xffffffff, (int32_t)(fv - (ev + 3)) >= 0) & 7) & todo;
            todo &= ~m;
            while (m) {
              const uint32_t i = __ffs(m) - 1, bb = i / 3, slot = (0x176054321ull >> (4 * i)) & 7, bytes = bb == 2 ? 6144 : 8192;
              m &= m - 1;
              if (elect_one()) {
                mbar_expect_tx(afull + slot * 8, bytes);
                bulk_g2s(abase + slot * 8192, hb + (r ^ (2 + 2 * (i - 3 * bb))) * 1536 + bb * 512, bytes, afull + slot * 8);
              }
            }
          }
          if (++cnt > SPIN_LIMIT * 16) __trap();
        }
        p0 ^= 1;
        __syncwarp();
      }
      if (l == 0) {
        mbar_wait(own + 16, po); po ^= 1;
        mbar_wait(afree, p0); p0 ^= 1;
        fetch_chunks<8, 1>(g_act + (2 * 32 + half) * 4096, flags, abase, afull, r, ev + 6, lane);
        gather_stats(g_stats + (2 * 32 + half) * 512, sb + SM_STAT + h * 512, sb + B_STAT + h * 8, lane, tag);
      }
    }
  } else {
    uint4 cv[8];
    colsum_load(cv, wqkv + 64 * r + 8 * (lane & 7), 3 * kD, true, 32 * cb, lane);
    if (lane < 24) { g_kv[(0 * 8 + r) * 384 + cb * 24 + lane] = make_float4(0.f, 0.f, 0.f, 0.f); g_kv[(1 * 8 + r) * 384 + cb * 24 + lane] = make_float4(0.f, 0.f, 0.f, 0.f); }
    fence_gpu();
    const uint32_t tag = (epoch & 1) ^ 1;
    colsum_publish(cv, g_cs + ((r * 2 + 0) * 16 + cb) * 48 + 2 * (lane & 7), lane, tag);
    mbar_wait(sb + B_AFULL + (first_chunk(1, r) ^ r) * 8, 0);
    colsum_gather(g_cs + (r * 2 + 0) * 16 * 48, sb + SM_CS, 0, 1, 48, lane, tag);
    if (lane == 0) mbar_arrive(sb + B_CSQ);
    if (lane == 1) prefetch_l2((const char*)wo + bid * 4096, 4096);
    if (lane == 2) prefetch_l2((const char*)w2 + bid * 11008, 11008);
    asm volatile("barrier.cluster.wait.aligned;" ::: "memory");
#pragma unroll 1
    for (int l = 0; l < 2; l++) {
      mbar_wait(sb + B_KVDONE, l);
      const float4* kv = g_kv + (l * 8 + r) * 384 + lane;
      float4 v[12];
      uint32_t cnt = 0;
      spin(kKvDelay);
      while (true) {
        bool ok = true;
#pragma unroll
        for (int i = 0; i < 12; i++) v[i] = ld_relaxed_f4(kv + i * 32);
#pragma unroll
        for (int i = 0; i < 12; i++) ok = ok && v[i].w == 16.f;
        if (__all_sync(0xffffffff, ok)) break;
        const float4* pp = g_kv + (l * 8 + r) * 384 + (lane & 3) * 96 + 95;
        while (!__all_sync(0xffffffff, ld_relaxed_f4(pp).w == 16.f)) { if (++cnt > SPIN_LIMIT) __trap(); }
        if (++cnt > SPIN_LIMIT) __trap();
      }
#pragma unroll
      for (int hh = 0; hh < 4; hh++) {
        const float4 a = v[3 * hh], b = v[3 * hh + 1], c = v[3 * hh + 2];
        const float z0 = __shfl_sync(0xffffffff, c.z, lane & 3), z1 = __shfl_sync(0xffffffff, c.z, 4 + (lane & 3)),
                    z2 = __shfl_sync(0xffffffff, c.z, 8 + (lane & 3)), z3 = __shfl_sync(0xffffffff, c.z, 12 + (lane & 3));
        const uint32_t d = sb + SM_RING + 16384 + hh * 768 + lane * 8;
        sts_u2(d, pack_bf16(a.x, a.y), pack_bf16(a.z, b.x));
        sts_u2(d + 256, pack_bf16(b.y, b.z), pack_bf16(c.x, c.y));
        sts_u2(d + 512, pack_bf16(z0, z1), pack_bf16(z2, z3));
      }
      __syncwarp();
      if (lane == 0) mbar_arrive(sb + B_KVRDY);
      if (l == 0) {
        colsum_gather(g_cs + (r * 2 + 1) * 16 * 48, sb + SM_CS + 768, 0, 3, 44, lane, tag);
        if (lane == 0) mbar_arrive(sb + B_CSRDY + 8);
      }
      mbar_wait(sb + B_HPUB, l); mbar_wait(sb + B_HPUB + 8, l);
      mbar_wait(sb + B_OWN + 8, l); mbar_wait(sb + B_OWN + 24 + 8, l);
#pragma unroll 1
      for (int bb = 1; bb < 3; bb++) {
        if (lane == 0) {
          char* dst = (char*)(g_h + (cb * 2 * 8 + r) * 1536) + bb * 8192;
#pragma unroll 1
          for (int o = 0; o < (bb == 1 ? 8192 : 6144); o += 1024) {
            bulk_s2g(dst + o, sb + (5 + bb) * 8192 + o, 1024); bulk_commit(); bulk_wait_read<3>();
            bulk_s2g(dst + 8 * 1536 * 16 + o, sb + 65536 + (5 + bb) * 8192 + o, 1024); bulk_commit(); bulk_wait_read<3>();
          }
          bulk_wait_read<0>();
          mbar_arrive(sb + B_HP1 + (bb - 1) * 8);
          if (bb == 2) { mbar_arrive(sb + B_AFREE + 8); mbar_arrive(sb + B_AFREE + 24 + 8); }
        }
        __syncwarp();
      }
    }
    if (lane == 0) g_epoch[bid * 8] = epoch + 1;
  }
  } else {
    asm volatile("setmaxnreg.inc.sync.aligned.u32 208;");
    const int lane = __shfl_sync(0xffffffff, threadIdx.x & 31, threadIdx.x & 31);
    const int wg0 = warp >> 2, lane0 = lane, half = cb * 2 + wg0;
    const uint32_t sb0 = sb;
    uint4 cv[8];
    if ((warp & 3) == 1) colsum_load(cv, wqkv + (1 + wg0) * 512 + 64 * r + 8 * (lane & 7), 3 * kD, true, 32 * cb, lane);
    const uint32_t epoch = ld_relaxed(g_epoch + bid * 8);
    if ((warp & 3) == 1) colsum_publish(cv, g_cs + ((r * 2 + 0) * 16 + cb) * 48 + (1 + wg0) * 16 + 2 * (lane & 7), lane, (epoch + 1) & 1);
    const uint32_t tag = (epoch + 1) & 1;
    uint32_t xr[16];
    uint32_t sph = 0;
    mbar_wait(sb0 + B_AFULL + wg0 * 64, 0);
#pragma unroll
    for (int s = 0; s < 4; s++)
      ldsm4(sb0 + wg0 * 65536 + (16 * (warp & 3) + 8 * ((lane0 >> 3) & 1) + (lane0 & 7)) * 128 + (((2 * s + (lane0 >> 4)) ^ (lane0 & 7)) << 4),
            xr[4 * s], xr[4 * s + 1], xr[4 * s + 2], xr[4 * s + 3]);
    asm volatile("barrier.cluster.wait.aligned;" ::: "memory");

#pragma unroll 1
    for (int l = 0; l < 2; l++) {
      const uint32_t sb = opaque(sb0);
      const int lane = opaque(lane0), wg = opaque(wg0), wq = opaque(warp) & 3, g = lane >> 2, t = lane & 3;
      const uint32_t abase = sb + wg * 65536, afull = sb + B_AFULL + wg * 64, afree = sb + B_AFREE + wg * 24, own = sb + B_OWN + wg * 24;
      const uint32_t ring = sb + SM_RING;
      const uint32_t dA = desc_lo(abase, 16), dH = desc_lo(abase, 1024), dB = desc_lo(ring, 8192);
      constexpr int S4 = SLOT >> 4;
      uint32_t swa[4];
#pragma unroll
      for (int s = 0; s < 4; s++) swa[s] = abase + (16 * wq + 8 * ((lane >> 3) & 1) + (lane & 7)) * 128 + (((2 * s + (lane >> 4)) ^ (lane & 7)) << 4);
      auto wait_b = [&](int st) { mbar_wait(sb + B_BFULL + st_slot(st) * 8, st_par(st)); };
      auto release_b = [&](int st) { if (lane == 0) mbar_arrive(sb + B_BEMPTY + st_slot(st) * 8); };
      auto signal = [&](uint32_t bar) { __syncwarp(); if (lane == 0) mbar_arrive(bar); };
      const uint32_t chk = abase + (16 * wq + g) * 128 + (((2 * t) ^ g) << 4);
      auto bad_chunk = [&](int i, uint32_t tg) -> uint32_t { return (lds_u32(chk + i * 8192) ^ tg) | (lds_u32(chk + (i * 8192 + 1024)) ^ tg); };
      auto apar = [&](int i, int ph) -> uint32_t { return ((l & (i == 2 || i == 3 ? 0 : 1)) ^ (i == 0 ? 1 : i < 4 || ph == 0 ? ph : ph - 1)) & 1; };
      auto fetch_ok = [&](int i, int n, int ph, int str, int buf, uint32_t tg) {
        uint32_t bad = 0;
#pragma unroll
        for (int u = i; u < i + n; u++) mbar_wait(afull + u * 8, apar(u, ph));
#pragma unroll
        for (int u = i; u < i + n; u++) bad |= bad_chunk(u, tg);
        if (__builtin_expect(!__all_sync(0xffffffff, (bad & 1u) == 0), 0)) {
#pragma unroll 1
          for (int u = i; u < i + n; u++) {
            const uint4* src = g_act + (buf * 32 + opaque(half)) * 4096 + (opaque(r) ^ (str * u)) * 512 + wq * 128 + opaque(lane);
            const uint32_t dst = abase + u * 8192 + wq * 2048 + opaque(lane) * 16;
            uint32_t cnt = 0;
            while (!__all_sync(0xffffffff, (bad_chunk(u, tg) & 1u) == 0)) {
              uint4 q[4];
#pragma unroll
              for (int v = 0; v < 4; v++) q[v] = ld_relaxed_u4(src + v * 32);
#pragma unroll
              for (int v = 0; v < 4; v++) sts_u4(dst + v * 512, q[v]);
              fence_async_smem();
              __syncwarp();
              if (++cnt > SPIN_LIMIT) __trap();
            }
          }
        }
      };
      const uint32_t hchk = abase + (lane >> 4) * 2048 + ((lane >> 3) & 1) * 1024 + (2 * wq + ((lane >> 2) & 1)) * 128 + (lane & 3) * 32 + g * 4;
      const uint32_t hchk3 = hchk + (lane >= 16 ? 0 : 4096);
      auto bad_block = [&](int slot, bool three, uint32_t tg) -> uint32_t {
        return (lds_u32(hchk + slot * 8192) ^ tg) | (lds_u32(three ? hchk3 + slot * 8192 : hchk + (slot * 8192 + 4096)) ^ tg);
      };
      auto refetch_h = [&](int slot, int ts, int bb, uint32_t tg) {
        const int ln = opaque(lane);
        const uint32_t off = (ln >> 4) * 1024 + wq * 256 + (ln & 15) * 16;
        const uint4* src = g_h + (opaque(half) * 8 + (opaque(r) ^ (2 * ts))) * 1536 + bb * 512 + off / 16;
        uint32_t cnt = 0;
        while (!__all_sync(0xffffffff, (bad_block(slot, bb == 2, tg) >> 31) == 0)) {
          uint4 q[4];
#pragma unroll
          for (int v = 0; v < 4; v++) q[v] = ld_relaxed_u4(src + (bb == 2 && v == 3 ? 2 : v) * 128);
#pragma unroll
          for (int v = 0; v < 4; v++) sts_u4(abase + slot * 8192 + (bb == 2 && v == 3 ? 2 : v) * 2048 + off, q[v]);
          fence_async_smem();
          __syncwarp();
          if (++cnt > SPIN_LIMIT) __trap();
        }
      };
      auto peer_ready = [&]() {
        if (lane == 0) { mbar_arrive_remote(mapa(sb + B_PFREE + wg * 8, (r & 1) ^ 1)); if (wq == 0) mbar_expect_tx(sb + B_PRDY + wg * 8, 8192); }
      };
      auto send_partial = [&](const float (&v)[32], uint32_t land) {
        const uint32_t rdst = mapa(abase + land + (wq * 32 + lane) * 16, (r & 1) ^ 1), rbar = mapa(sb + B_PRDY + wg * 8, (r & 1) ^ 1);
#pragma unroll
        for (int i = 0; i < 4; i++)
          st_async_v4(rdst + i * 2048, pack_bf16(v[8 * i], v[8 * i + 1]), pack_bf16(v[8 * i + 2], v[8 * i + 3]),
                      pack_bf16(v[8 * i + 4], v[8 * i + 5]), pack_bf16(v[8 * i + 6], v[8 * i + 7]), rbar);
      };
      auto add_residual = [&](const float (&v)[32], uint32_t land, uint32_t par, float a0, float a1) {
        mbar_wait(sb + B_PRDY + wg * 8, par);
        uint4 p[4];
#pragma unroll
        for (int i = 0; i < 4; i++) p[i] = lds_u4(abase + land + i * 2048 + (wq * 32 + lane) * 16);
#pragma unroll
        for (int i = 0; i < 4; i++) {
          xr[4 * i] = pack_bf16(fmaf(a0, v[8 * i] + bf_lo(p[i].x), bf_lo(xr[4 * i])), fmaf(a0, v[8 * i + 1] + bf_hi(p[i].x), bf_hi(xr[4 * i])));
          xr[4 * i + 1] = pack_bf16(fmaf(a1, v[8 * i + 2] + bf_lo(p[i].y), bf_lo(xr[4 * i + 1])), fmaf(a1, v[8 * i + 3] + bf_hi(p[i].y), bf_hi(xr[4 * i + 1])));
          xr[4 * i + 2] = pack_bf16(fmaf(a0, v[8 * i + 4] + bf_lo(p[i].z), bf_lo(xr[4 * i + 2])), fmaf(a0, v[8 * i + 5] + bf_hi(p[i].z), bf_hi(xr[4 * i + 2])));
          xr[4 * i + 3] = pack_bf16(fmaf(a1, v[8 * i + 6] + bf_lo(p[i].w), bf_lo(xr[4 * i + 3])), fmaf(a1, v[8 * i + 7] + bf_hi(p[i].w), bf_hi(xr[4 * i + 3])));
        }
      };
      const uint32_t tmask = t == 0 ? 1u : 0u;
      auto store_chunk = [&](const uint32_t (&v)[16], uint32_t tg  , uint32_t msk, int buf, uint32_t e) {
        uint4* gdst = g_act + (buf * 32 + opaque(half)) * 4096 + opaque(r) * 512;
        uint4* flag = g_flags + opaque(half) * 128 + opaque(r) * 2;
#pragma unroll
        for (int s = 0; s < 4; s++) stsm4(swa[s], (v[4 * s] & ~msk) | tg, (v[4 * s + 1] & ~msk) | tg, v[4 * s + 2], v[4 * s + 3]);
        fence_async_smem();
        wg_bar(wg);
        if (wq == 0) {
          if (buf == 3) { if (lane == 0) { tma_store(&tm_out, abase, 64 * r, 64 * half); bulk_commit(); bulk_wait<0>(); } }
          else {
            if (lane == 0) { bulk_s2g(gdst, abase, 8192); bulk_commit(); }
            __syncwarp();
            set_flags(flag, epoch * 16 + l * 6 + e, lane);
            if (lane == 0) mbar_arrive(own + 16);
          }
          __syncwarp();
        }
      };
      auto slot0_free = [&]() { if (wq == 0 && lane == 0) bulk_wait_read<0>(); __syncwarp(); };
      auto stat_dst = [&](int ln) -> float2* { return g_stats + (ln * 32 + opaque(half)) * 512 + opaque(r) * 64 + 16 * wq + g; };
      const uint32_t stat_sm = sb + SM_STAT + (wg * 64 + 16 * wq + g) * 8;
      const uint32_t cs_sm = sb + SM_CS + 8 * t;
      const uint32_t ltag = l ^ 1;
      float rs0, rs1;
      {
        float ak[32], av[32], aq[32];
        {
          wait_b(0);
          wg_fence();
          wgmma_n128_init<0, 0, HI_SW>(ak, av, dA, dB);
          static_for<1, 4>([&](auto K) { wgmma_n128<2 * K.value, 128 * K.value, HI_SW>(ak, av, dA, dB); });
          wg_commit();
          publish_stats(xr, stat_dst(2 * l), t, tag);
        }
#pragma unroll 1
        for (int i = 1; i < 8; i++) {
          const int slot = l == 0 ? first_chunk(i, r) ^ r : i;
          if (l == 0) mbar_wait(afull + slot * 8, 0); else fetch_ok(i, 1, 0, 1, 2, tag);
          mbar_wait(sb + B_BFULL + (i & 3) * 8, i >> 2);
          wg_fence();
          const uint32_t la = dA + slot * 512, lb = dB + (i & 3) * S4;
          static_for<0, 4>([&](auto K) { wgmma_n128<2 * K.value, 128 * K.value, HI_SW>(ak, av, la, lb); });
          wg_commit();
          wg_wait<1>(); if (lane == 0) mbar_arrive(sb + B_BEMPTY + ((i - 1) & 3) * 8);
        }
        auto q_stage = [&](auto I) {
          constexpr int i = I.value;
          wait_b(8 + i);
          wg_fence();
          static_for<0, 8>([&](auto K) {
            constexpr int k = K.value;
            if constexpr (i == 0 && k == 0) wgmma_n64_init<0, 0, HI_SW>(aq, dA, dB);
            else wgmma_n64<i * 1024 + (k >> 2) * 512 + 2 * (k & 3), i * S4 + 128 * k, HI_SW>(aq, dA, dB);
          });
          wg_commit();
        };
        if (l == 0) mbar_wait(sb + B_CSRDY, 0);
        mbar_wait(sb + B_STAT + wg * 8, sph); sph ^= 1;
        const float2 s0 = lds_f2(stat_sm), s1 = lds_f2(stat_sm + 64);
        const float y0 = s0.x * 1.4426950408889634f, y1 = s1.x * 1.4426950408889634f;
        const uint32_t pk_s = ring + (2 * wg) * SLOT + 16384;
        {
          float2 c[16];
#pragma unroll
          for (int j = 0; j < 16; j++) c[j] = lds_f2(cs_sm + (64 + 8 * j) * 4);
          wg_wait<0>(); release_b(7);
          fence_regs(ak); fence_regs(av);
          uint32_t pk[16], pv[16];
#pragma unroll
          for (int j = 0; j < 8; j++) {
            pk[2 * j] = pack_bf16(phi_y(y0 * fmaf(s0.y, c[j].x, ak[4 * j])), phi_y(y0 * fmaf(s0.y, c[j].y, ak[4 * j + 1])));
            pk[2 * j + 1] = pack_bf16(phi_y(y1 * fmaf(s1.y, c[j].x, ak[4 * j + 2])), phi_y(y1 * fmaf(s1.y, c[j].y, ak[4 * j + 3])));
            pv[2 * j] = pack_bf16(s0.x * fmaf(s0.y, c[8 + j].x, av[4 * j]), s0.x * fmaf(s0.y, c[8 + j].y, av[4 * j + 1]));
            pv[2 * j + 1] = pack_bf16(s1.x * fmaf(s1.y, c[8 + j].x, av[4 * j + 2]), s1.x * fmaf(s1.y, c[8 + j].y, av[4 * j + 3]));
          }
#pragma unroll
          for (int s = 0; s < 4; s++) {
            stsm4(swa[s] + (pk_s - abase), pk[4 * s], pk[4 * s + 1], pk[4 * s + 2], pk[4 * s + 3]);
            stsm4(swa[s] + (pk_s - abase) + SLOT, pv[4 * s], pv[4 * s + 1], pv[4 * s + 2], pv[4 * s + 3]);
          }
        }
        slot0_free();
        if (wg == 0) { asm volatile("bar.arrive 4, 256;" ::: "memory"); asm volatile("bar.sync 5, 256;" ::: "memory"); }
        else {
          if (l == 0) mbar_wait(sb + B_CSQ, 0);
          asm volatile("bar.sync 4, 256;" ::: "memory");
          float cc[2][4][4];
#pragma unroll
          for (int u = 0; u < 32; u++) cc[u >> 4][(u >> 2) & 3][u & 3] = 0.f;
          const int m = lane >> 3;
          const uint32_t va = ring + SLOT + 16384 + (8 * (m >> 1) + (lane & 7)) * 128 + (((2 * wq + (m & 1)) ^ (lane & 7)) << 4);
          const uint32_t pa = ring + 16384 + (8 * (m & 1) + (lane & 7)) * 128 + (((2 * wq + (m >> 1)) ^ (lane & 7)) << 4);
#pragma unroll
          for (int ks = 0; ks < 8; ks++) {
            uint32_t a0, a1, a2, a3, b0, b1, b2, b3;
            ldsm4t(va + (ks & 1) * 2 * SLOT + (ks >> 1) * 2048, a0, a1, a2, a3);
            ldsm4t(pa + (ks & 1) * 2 * SLOT + (ks >> 1) * 2048, b0, b1, b2, b3);
            mma16816(cc[ks & 1][0], a0, a1, a2, a3, b0, b1);
            mma16816(cc[ks & 1][1], a0, a1, a2, a3, b2, b3);
            mma16816(cc[ks & 1][2], 0x3f803f80u, 0x3f803f80u, 0x3f803f80u, 0x3f803f80u, b0, b1);
            mma16816(cc[ks & 1][3], 0x3f803f80u, 0x3f803f80u, 0x3f803f80u, 0x3f803f80u, b2, b3);
          }
          float c0[4], c1[4], z0[2], z1[2];
#pragma unroll
          for (int u = 0; u < 4; u++) { c0[u] = cc[0][0][u] + cc[1][0][u]; c1[u] = cc[0][1][u] + cc[1][1][u]; }
#pragma unroll
          for (int u = 0; u < 2; u++) { z0[u] = cc[0][2][u] + cc[1][2][u]; z1[u] = cc[0][3][u] + cc[1][3][u]; }
          asm volatile("bar.arrive 5, 256;" ::: "memory");
          float* kv = (float*)(g_kv + (l * 8 + opaque(r)) * 384 + wq * 96 + lane);
          red_add_f4(kv, c0[0], c0[1], c1[0], 1.f);
          red_add_f4(kv + 128, c1[1], c0[2], c0[3], 1.f);
          red_add_f4(kv + 256, c1[2], c1[3], g == 0 ? z0[0] : g == 1 ? z0[1] : g == 2 ? z1[0] : z1[1], 1.f);
          signal(sb + B_KVDONE);
        }
        q_stage(IC<0>{}); q_stage(IC<1>{}); q_stage(IC<2>{}); q_stage(IC<3>{});
        float2 c[8];
        if (l == 0) mbar_wait(sb + B_CSQ, 0);
#pragma unroll
        for (int j = 0; j < 8; j++) c[j] = lds_f2(cs_sm + 8 * j * 4);
        wg_wait<3>(); release_b(8);
        wg_wait<2>(); release_b(9);
        wg_wait<1>(); release_b(10);
        wg_wait<0>(); release_b(11);
        fence_regs(aq);
        if (lane == 0) mbar_arrive(afree);
        peer_ready();
        uint32_t pq[16];
#pragma unroll
        for (int j = 0; j < 8; j++) {
          pq[2 * j] = pack_bf16(phi_y(y0 * fmaf(s0.y, c[j].x, aq[4 * j])), phi_y(y0 * fmaf(s0.y, c[j].y, aq[4 * j + 1])));
          pq[2 * j + 1] = pack_bf16(phi_y(y1 * fmaf(s1.y, c[j].x, aq[4 * j + 2])), phi_y(y1 * fmaf(s1.y, c[j].y, aq[4 * j + 3])));
        }
        mbar_wait(sb + B_KVRDY, l);
        if (wg == 1) spin(kSkew);
        uint2 f[12];
#pragma unroll
        for (int i = 0; i < 12; i++) f[i] = lds_u2(ring + 16384 + i * 256 + lane * 8);
        float cn[4][8], cz[4][4];
#pragma unroll
        for (int hh = 0; hh < 4; hh++) {
          float c0[4] = {0.f, 0.f, 0.f, 0.f}, c1[4] = {0.f, 0.f, 0.f, 0.f};
          cz[hh][0] = cz[hh][1] = cz[hh][2] = cz[hh][3] = 0.f;
          mma16816(cz[hh], pq[4 * hh], pq[4 * hh + 1], pq[4 * hh + 2], pq[4 * hh + 3], f[3 * hh + 2].x, f[3 * hh + 2].y);
          mma16816(c0, pq[4 * hh], pq[4 * hh + 1], pq[4 * hh + 2], pq[4 * hh + 3], f[3 * hh].x, f[3 * hh].y);
          mma16816(c1, pq[4 * hh], pq[4 * hh + 1], pq[4 * hh + 2], pq[4 * hh + 3], f[3 * hh + 1].x, f[3 * hh + 1].y);
#pragma unroll
          for (int u = 0; u < 4; u++) { cn[hh][u] = c0[u]; cn[hh][4 + u] = c1[u]; }
        }
        uint32_t o[16];
#pragma unroll
        for (int hh = 0; hh < 4; hh++) {
          const float i0 = rcp(cz[hh][0] + 1e-6f), i1 = rcp(cz[hh][2] + 1e-6f);
          o[4 * hh] = pack_bf16(cn[hh][0] * i0, cn[hh][1] * i0); o[4 * hh + 1] = pack_bf16(cn[hh][2] * i1, cn[hh][3] * i1);
          o[4 * hh + 2] = pack_bf16(cn[hh][4] * i0, cn[hh][5] * i0); o[4 * hh + 3] = pack_bf16(cn[hh][6] * i1, cn[hh][7] * i1);
        }
        store_chunk(o, ltag & tmask, tmask, 0, 1);
      }
      {
        float ap[32], ao[32];
        wait_b(12);
        wg_fence();
        wgmma_n64_init<0, 0, HI_SW>(ap, dA, dB);
        static_for<1, 4>([&](auto K) { wgmma_n64<2 * K.value, 128 * K.value, HI_SW>(ap, dA, dB); });
        wgmma_n64_init<0, 512, HI_SW>(ao, dA, dB);
        static_for<1, 4>([&](auto K) { wgmma_n64<2 * K.value, 512 + 128 * K.value, HI_SW>(ao, dA, dB); });
        wg_commit();
        wait_b(13);
        wg_wait<0>(); release_b(12);
        slot0_free();
        wg_bar(wg);
        fetch_ok(1, 1, 1, 2, 0, ltag);
        wg_fence();
        static_for<0, 4>([&](auto K) { wgmma_n64<512 + 2 * K.value, S4 + 128 * K.value, HI_SW>(ap, dA, dB); });
        static_for<0, 4>([&](auto K) { wgmma_n64<512 + 2 * K.value, S4 + 512 + 128 * K.value, HI_SW>(ao, dA, dB); });
        wg_commit();
        wait_b(14); wait_b(15);
        wg_wait<0>(); release_b(13);
        static_for<2, 4>([&](auto I) {
          constexpr int i = I.value;
          fetch_ok(i, 1, 1, 2, 0, ltag);
          wg_fence();
          static_for<0, 4>([&](auto K) { wgmma_n64<i * 512 + 2 * K.value, i * S4 + 128 * K.value, HI_SW>(ap, dA, dB); });
        });
        wg_commit();
        static_for<0, 2>([&](auto K) { wgmma_n64<2 * 512 + 2 * K.value, 2 * S4 + 512 + 128 * K.value, HI_SW>(ao, dA, dB); });
        wg_commit();
        mbar_wait(sb + B_PFREE + wg * 8, 0);
        wg_wait<1>();
        fence_regs(ap);
        send_partial(ap, 4 * 8192);
        wg_fence();
        static_for<2, 8>([&](auto K) { wgmma_n64<(2 + K.value / 4) * 512 + 2 * (K.value & 3), (2 + K.value / 4) * S4 + 512 + 128 * (K.value & 3), HI_SW>(ao, dA, dB); });
        wg_commit();
        wg_wait<0>(); release_b(14); release_b(15);
        fence_regs(ao);
        add_residual(ao, 4 * 8192, 0, 1.f, 1.f);
        signal(afree);
        store_chunk(xr, ltag & tmask, tmask, 1, 2);
      }
      {
        float g0[32], g1[56], h0[32], h1[56];
        wait_b(16);
        wg_fence();
        wgmma_n176_init<0, 0, HI_SW>(g0, g1, dA, dB);
        static_for<1, 4>([&](auto K) { wgmma_n176<2 * K.value, 128 * K.value, HI_SW>(g0, g1, dA, dB); });
        wg_commit();
        publish_stats(xr, stat_dst(2 * l + 1), t, tag);
#pragma unroll 1
        for (int i = 1; i < 7; i++) {
          fetch_ok(i, 1, 2, 1, 1, ltag);
          mbar_wait(sb + B_BFULL + (i & 3) * 8, i >> 2);
          wg_fence();
          const uint32_t la = dA + i * 512, lb = dB + (i & 3) * S4;
          static_for<0, 4>([&](auto K) { wgmma_n176<2 * K.value, 128 * K.value, HI_SW>(g0, g1, la, lb); });
          wg_commit();
          wg_wait<1>(); if (lane == 0) mbar_arrive(sb + B_BEMPTY + ((i - 1) & 3) * 8);
        }
        fetch_ok(7, 1, 2, 1, 1, ltag);
        wait_b(23);
        wg_wait<0>(); release_b(22);
        if (lane == 0) mbar_arrive(sb + B_EARLY + wg * 8);
        fence_regs(g0); fence_regs(g1);
        rename_regs(h0, g0); rename_regs(h1, g1);
        wg_fence();
        static_for<0, 4>([&](auto K) { wgmma_n64<7 * 512 + 2 * K.value, 3 * S4 + 128 * K.value, HI_SW>(h0, dA, dB); });
        wg_commit();
        if (l == 0) mbar_wait(sb + B_CSRDY + 8, 0);
        mbar_wait(sb + B_STAT + wg * 8, sph); sph ^= 1;
        const float2 s0 = lds_f2(stat_sm), s1 = lds_f2(stat_sm + 64);
        float2 c[22];
#pragma unroll
        for (int j = 0; j < 22; j++) c[j] = lds_f2(cs_sm + (192 + 8 * j) * 4);
        const uint32_t sgn = ltag ? 0x80008000u : 0u;
        rs0 = ltag ? -s0.x : s0.x; rs1 = ltag ? -s1.x : s1.x;
        const uint32_t hrow = abase + (lane >> 4) * 1024 + (2 * wq + ((lane >> 3) & 1)) * 128 + (lane & 7) * 16;
        auto store_h = [&](const float* a, const float2* cc, int nt, uint32_t dst) {
          uint32_t p[16];
#pragma unroll
          for (int j = 0; j < nt; j++) {
            p[2 * j] = pack_bf16_relu(fmaf(s0.y, cc[j].x, a[4 * j]), fmaf(s0.y, cc[j].y, a[4 * j + 1])) ^ sgn;
            p[2 * j + 1] = pack_bf16_relu(fmaf(s1.y, cc[j].x, a[4 * j + 2]), fmaf(s1.y, cc[j].y, a[4 * j + 3])) ^ sgn;
          }
#pragma unroll
          for (int s = 0; s < nt / 2; s++) stsm4(dst + s * 2048, p[4 * s], p[4 * s + 1], p[4 * s + 2], p[4 * s + 3]);
        };
        slot0_free();
        wg_bar(wg);
        wg_wait<0>();
        fence_regs(h0);
        store_h(h0, c, 8, hrow);
        fence_async_smem();
        signal(own);
        wg_fence();
        static_for<0, 4>([&](auto K) { wgmma_n112<7 * 512 + 2 * K.value, 3 * S4 + 512 + 128 * K.value, HI_SW>(h1, dA, dB); });
        wg_commit();
        wg_wait<0>(); release_b(23);
        fence_regs(h1);
        if (lane == 0) mbar_arrive(afree);
        wg_bar(wg);
        store_h(h1, c + 8, 8, hrow + 6 * 8192);
        store_h(h1 + 32, c + 16, 6, hrow + 7 * 8192);
        fence_async_smem();
        signal(own + 8);
        wg_bar(wg);
      }
      {
        float ap[32], ao[32];
        float bp[32], bo[32];
        const uint32_t htag = ltag << 31;
        static_for<0, 3>([&](auto B) {
          constexpr int b = B.value;
          wait_b(24 + b);
          wg_fence();
          static_for<0, (b == 2 ? 3 : 4)>([&](auto K) {
            if constexpr (b == 0 && K.value == 0) wgmma_n128_init<0, 0, HI_NS>(ap, ao, dH, dB);
            else wgmma_n128<(b ? 5 + b : 0) * 512 + 128 * K.value, b * 1024 + 128 * K.value, HI_NS>(ap, ao, dH, dB);
          });
          wg_commit();
          if (b > 0) { wg_wait<1>(); release_b(23 + b); }
        });
        wg_wait<0>(); release_b(26);
        if (lane == 0) mbar_arrive(afree + 8);
        static_for<0, 6>([&](auto I) {
          constexpr int i = I.value, slot = (1 + i) % 6;
          mbar_wait(afull + slot * 8, apar(slot, 3));
          if (__builtin_expect(!__all_sync(0xffffffff, (bad_block(slot, false, htag) >> 31) == 0), 0)) refetch_h(slot, 1 + i % 3, i / 3, htag);
          wait_b(27 + i);
          wg_fence();
          static_for<0, 4>([&](auto K) { wgmma_n128<slot * 512 + 128 * K.value, (st_off(27 + i) >> 4) + 128 * K.value, HI_NS>(ap, ao, dH, dB); });
          wg_commit();
          if (i > 0) { wg_wait<1>(); release_b(26 + i); }
          if (i == 1 && lane == 0) mbar_arrive(afree + 16);
          if (i == 2) peer_ready();
        });
        mbar_wait(afull + 48, apar(6, 3)); mbar_wait(afull + 56, apar(7, 3)); mbar_wait(afull + 8, apar(1, 4));
        if (__builtin_expect(!__all_sync(0xffffffff, ((bad_block(6, true, htag) | bad_block(7, true, htag) | bad_block(1, true, htag)) >> 31) == 0), 0)) {
#pragma unroll 1
          for (int u = 1; u < 4; u++) refetch_h(u == 3 ? 1 : 5 + u, u, 2, htag);
        }
        wait_b(33); wait_b(34); wait_b(35);
        wg_wait<0>(); release_b(32);
        fence_regs(ap); fence_regs(ao);
        rename_regs(bp, ap); rename_regs(bo, ao);
        auto last = [&](float (&acc)[32], auto K, auto OWN) {
          constexpr int b = K.value / 3, k = K.value % 3;
          wgmma_n64<(b == 2 ? 1 : 6 + b) * 512 + 128 * k, (3 + b) * 1024 + OWN.value * 512 + 128 * k, HI_NS>(acc, dH, dB);
        };
        wg_fence();
        static_for<0, 9>([&](auto K) { last(bp, K, IC<0>{}); });
        wg_commit();
        static_for<0, 2>([&](auto K) { last(bo, K, IC<1>{}); });
        wg_commit();
        mbar_wait(sb + B_PFREE + wg * 8, 1);
        wg_wait<1>();
        fence_regs(bp);
        send_partial(bp, 2 * 8192);
        wg_fence();
        static_for<2, 9>([&](auto K) { last(bo, K, IC<1>{}); });
        wg_commit();
        wg_wait<0>(); release_b(33); release_b(34); release_b(35);
        wg_bar(wg);
        fence_regs(bo);
        add_residual(bo, 2 * 8192, 1, rs0, rs1);
        {
          signal(afree);
          store_chunk(xr, l == 0 ? (tag & tmask) : 0u, l == 0 ? tmask : 0u, l == 0 ? 2 : 3, 6);
        }
      }
    }
  }
}

typedef CUresult (*EncodeFn)(CUtensorMap*, CUtensorMapDataType, cuuint32_t, void*, const cuuint64_t*, const cuuint64_t*, const cuuint32_t*,
                             const cuuint32_t*, CUtensorMapInterleave, CUtensorMapSwizzle, CUtensorMapL2promotion, CUtensorMapFloatOOBfill);

CUtensorMap make_map(EncodeFn enc, const void* ptr, uint64_t cols, uint64_t rows, uint32_t box_rows) {
  CUtensorMap m;
  cuuint64_t gd[2] = {cols, rows}, gs[1] = {cols * 2};
  cuuint32_t bd[2] = {64, box_rows}, es[2] = {1, 1};
  enc(&m, CU_TENSOR_MAP_DATA_TYPE_BFLOAT16, 2, const_cast<void*>(ptr), gd, gs, bd, es, CU_TENSOR_MAP_INTERLEAVE_NONE,
      CU_TENSOR_MAP_SWIZZLE_128B, CU_TENSOR_MAP_L2_PROMOTION_L2_128B, CU_TENSOR_MAP_FLOAT_OOB_FILL_NONE);
  return m;
}

}

extern "C" void kernel_launch(void* const* d_in, const int* in_sizes, int n_in, void* d_out, int out_size) {
  (void)in_sizes; (void)n_in; (void)out_size;
  const __nv_bfloat16* x = (const __nv_bfloat16*)d_in[0];
  const __nv_bfloat16* wqkv = (const __nv_bfloat16*)d_in[1];
  const __nv_bfloat16* wo = (const __nv_bfloat16*)d_in[2];
  const __nv_bfloat16* w1 = (const __nv_bfloat16*)d_in[4];
  const __nv_bfloat16* w2 = (const __nv_bfloat16*)d_in[5];
  void* fn = nullptr;
  cudaDriverEntryPointQueryResult q;
  cudaGetDriverEntryPoint("cuTensorMapEncodeTiled", &fn, cudaEnableDefault, &q);
  EncodeFn enc = (EncodeFn)fn;
  const CUtensorMap tm_x = make_map(enc, x, kD, kS, 64), tm_out = make_map(enc, d_out, kD, kS, 64),
                    tm_wqkv = make_map(enc, wqkv, 3 * kD, kD, 64), tm_wo = make_map(enc, wo, kD, kD, 64),
                    tm_w1 = make_map(enc, w1, kFF, kD, 64), tm_w2 = make_map(enc, w2, kD, kFF, 64), tm_w2s = make_map(enc, w2, kD, kFF, 48);
  cudaFuncSetAttribute(fused_kernel, cudaFuncAttributeMaxDynamicSharedMemorySize, SM_TOTAL);
  fused_kernel<<<128, 384, SM_TOTAL>>>(tm_x, tm_out, tm_wqkv, tm_wo, tm_w1, tm_w2, tm_w2s, wqkv, wo, w1, w2);
}
```
